```python
import torch

def _softmax(x, axis=-1):
    return torch.softmax(x, dim=axis)
def _gelu(x):
    return torch.nn.functional.gelu(x, approximate="tanh")
def _silu(x):
    return torch.nn.functional.silu(x)
def _sigmoid(x):
    return torch.sigmoid(x)
def _layernorm(x, axis=-1, eps=1e-5):
    m = x.mean(dim=axis, keepdim=True)
    v = x.var(dim=axis, keepdim=True, unbiased=False)
    return (x - m) / torch.sqrt(v + eps)
def _scatter_add(tgt, idx, src, axis=0):
    return tgt.clone().index_add_(axis, idx, src)
def _segment_sum(src, seg, n):
    out = torch.zeros((n,) + src.shape[1:], dtype=src.dtype)
    return out.index_add_(0, seg, src)
def _pad(x, pw):
    flat = tuple(v for pair in reversed(pw) for v in pair)
    return torch.nn.functional.pad(x, flat)

kernel_name = 'sequential_preLN__mha_block_cached__glu_gated_geglu__decode'

def setup_inputs():

    _w = (lambda a: (lambda t: t.to(torch.bfloat16) if t.is_floating_point() else t)(torch.as_tensor(a)))
    def _A_setup():
        B, Sq, D = 4, 1, 576
        H, Sk, Dh = 32, 8192, 128
        return {
            "x": _w((lambda *s: torch.randn(*s, dtype=torch.bfloat16) * 0.05)(B, Sq, D)),
            "k_cache": _w((lambda *s: torch.randn(*s, dtype=torch.bfloat16) * 1.6)(B, H, Sk, Dh)),
            "v_cache": _w((lambda *s: torch.randn(*s, dtype=torch.bfloat16) * 0.8)(B, H, Sk, Dh)),
            "wq": _w((lambda *s: torch.randn(*s, dtype=torch.bfloat16) * 1.6)(D, H * Dh) * (D ** -0.5)),
            "wo": _w((lambda *s: torch.randn(*s, dtype=torch.bfloat16) * 0.8)(H * Dh, D) * ((H * Dh) ** -0.5)),
        }
    _A_in = _A_setup()

    def _B_setup():
        B, S, Dm, Df = 4, 1, 576, 4608
        return {
            "x": _w((lambda *s: torch.randn(*s, dtype=torch.bfloat16) * 0.05)(B, S, Dm)),
            "w_gate": _w((lambda *s: torch.randn(*s, dtype=torch.bfloat16) * 0.8)(Dm, Df) * (Dm ** -0.5)),
            "w_up": _w((lambda *s: torch.randn(*s, dtype=torch.bfloat16) * 0.8)(Dm, Df) * (Dm ** -0.5)),
            "w_down": _w((lambda *s: torch.randn(*s, dtype=torch.bfloat16) * 0.8)(Df, Dm) * (Df ** -0.5)),
        }
    _B_in = _B_setup()

    return {
        "A_x": _A_in["x"],
        "A_k_cache": _A_in["k_cache"],
        "A_v_cache": _A_in["v_cache"],
        "A_wq": _A_in["wq"],
        "A_wo": _A_in["wo"],
        "B_x": _B_in["x"],
        "B_w_gate": _B_in["w_gate"],
        "B_w_up": _B_in["w_up"],
        "B_w_down": _B_in["w_down"],
    }

def reference(A_x, A_k_cache, A_v_cache, A_wq, A_wo, B_x, B_w_gate, B_w_up, B_w_down):
    def _A_ref(x, k_cache, v_cache, wq, wo):
        B, Sq, D = x.shape
        H, Dh = 32, 128
        q = (lambda x, *d: x.permute(*d))((x @ wq).reshape(B, Sq, H, Dh), 0, 2, 1, 3)
        scores = torch.einsum("bhqd,bhkd->bhqk", q, k_cache) * (Dh ** -0.5)
        p = _softmax(scores, axis=-1)
        o = torch.einsum("bhqk,bhkd->bhqd", p, v_cache)
        return (lambda x, *d: x.permute(*d))(o, 0, 2, 1, 3).reshape(B, Sq, H * Dh) @ wo

    def _B_ref(x, w_gate, w_up, w_down):
        g = torch.einsum("bsd,df->bsf", x, w_gate)
        u = torch.einsum("bsd,df->bsf", x, w_up)
        h = _gelu(g) * u
        return torch.einsum("bsf,fd->bsd", h, w_down)

    x = A_x
    h = x + _A_ref(_layernorm(x, axis=-1), A_k_cache, A_v_cache, A_wq, A_wo)
    h2 = h + _B_ref(_layernorm(h, axis=-1), B_w_gate, B_w_up, B_w_down)
    return h2
```

```cpp
#include <cuda_runtime.h>
#include <cuda_bf16.h>
#include <cuda.h>
#include <stdint.h>
#include <type_traits>

#define EXP_MODE 0
namespace {

constexpr int NB = 4, DM = 576, NH = 32, SK = 8192, DH = 128, DF = 4608;
constexpr int NBH = NB * NH;
constexpr int TILE = 128;
constexpr int TILE_BYTES = TILE * DH * 2;
constexpr int NPAIR = 3;
constexpr int NTILES = SK / TILE;
#define CFG_SCHED 0
#define CFG_LEVELS 4, 4, 2, 2, 1, 1, 1, 1
constexpr int LEV[] = {CFG_LEVELS};
constexpr int NLEV = sizeof(LEV) / sizeof(int);
constexpr int lev_sum(int n) { return n == 0 ? 0 : LEV[n - 1] + lev_sum(n - 1); }
constexpr int L0 = NTILES - lev_sum(NLEV);
constexpr unsigned long long lev_pack(int n, bool start) {
    return n == 0 ? 0ull : (lev_pack(n - 1, start) | ((unsigned long long)(start ? lev_sum(n - 1) : LEV[n - 1]) << (5 * (n - 1))));
}
constexpr unsigned long long LEV_SIZE = lev_pack(NLEV, false), LEV_START = lev_pack(NLEV, true);
static_assert(NLEV <= 12 && lev_sum(NLEV) < 32 && LEV[0] > NPAIR, "schedule");
constexpr int NPOOL = NLEV * NBH;
constexpr int NSLOT = NLEV + 1;
#define CFG_TWO 380
#define CFG_TZ 640
constexpr int T_WO = NPOOL - CFG_TWO;
constexpr int T_ZERO = NPOOL - CFG_TZ;
constexpr int PART_STRIDE = 136;
constexpr int N_OWN = 36;
#define CFG_HREP 4
constexpr int H_REP = CFG_HREP;
#define CFG_HARM 6
constexpr int H_ARM = CFG_HARM;
constexpr int N_FFN = 96;
constexpr int FC = DF / N_FFN;
#define CFG_GUP 96
constexpr int GU_PITCH = CFG_GUP;
constexpr int GU_BOXROWS = 144;
constexpr int GU_BOX_BYTES = GU_BOXROWS * GU_PITCH;
#define CFG_NF 2
#define CFG_NFW 3
#define CFG_NFS 1
#define CFG_NFSS 1
constexpr int NF_START = CFG_NFS, NF_START_SLOTS = CFG_NFSS;
#define CFG_CLAIM 2
constexpr int CLAIM_AHEAD = CFG_CLAIM;
#define CFG_NFE 4
#define CFG_TE 128
constexpr int NF_END = CFG_NFE, T_END = NPOOL - CFG_TE;
#define CFG_HOLD 70
#define CFG_HOLD0 0
#define CFG_NFWO 8
constexpr int HOLD = CFG_HOLD;
constexpr int NFWO = CFG_NFWO;
constexpr int NF = CFG_NF;
constexpr int NFW = CFG_NFW;
constexpr int W_PITCH = DM * 2 + 16;
constexpr int NCONS = 256;
constexpr int NTHREADS = NCONS + 64;

constexpr int OFF_Q = 2 * NPAIR * TILE_BYTES;
constexpr int OFF_DESC = OFF_Q + 8 * 256;
constexpr int OFF_BAR = OFF_DESC + 8 * 16;
constexpr int OFF_TAG = OFF_BAR + 256;
constexpr int OFF_RED = OFF_TAG + 16;
constexpr int OFF_U = OFF_RED + 2 * 8 * PART_STRIDE * 4;
constexpr int OFF_XN = OFF_U;
constexpr int OFF_QRED = OFF_XN + DM * 16;
constexpr int HN_PITCH = 584;
constexpr int OFF_HN = OFF_U;
constexpr int OFF_GU = OFF_HN + 4 * HN_PITCH * 2;
constexpr int ACT_PITCH = 56;
constexpr int OFF_ACT = OFF_GU + 2 * 4 * FC * 4 * 4;
constexpr int OB_PITCH = 136;
constexpr int OFF_OB = OFF_ACT + 4 * ACT_PITCH * 2;
constexpr int OFF_ORED = OFF_GU;
constexpr int OFF_FLAG = OFF_OB + 4 * OB_PITCH * 2;
#define CFG_WOPRE 5
constexpr int WO_PRE = CFG_WOPRE;
constexpr int GRID = N_FFN + N_OWN;
constexpr int SMEM_BYTES = OFF_QRED + 8 * 128 * 4;
static_assert(OFF_FLAG + 16 <= SMEM_BYTES, "smem");
static_assert(SMEM_BYTES <= 232448, "smem");

constexpr int BAR_FULL = 0, BAR_EMPTY = 6, BAR_DESC = 12, BAR_W = 20, BAR_ZERO = 31;

constexpr float LOG2E = 1.4426950408889634f;
constexpr float SM_SCALE = 0.08838834764831845f;
constexpr float LN_EPS = 1e-5f;

struct alignas(128) Ctr { unsigned v; unsigned pad[31]; };
__device__ Ctr g_pool, g_done, g_epoch;
__device__ __align__(128) uint32_t g_q[NBH * DH / 2];
__device__ __align__(128) float g_part[NBH * NSLOT * PART_STRIDE];
__device__ __align__(128) float g_att[N_OWN * NH * 64];
__device__ __align__(128) uint32_t g_h[H_REP * NB * DM / 2];
__device__ __align__(128) float g_y[N_OWN * N_FFN * 64];
__device__ __align__(128) uint32_t g_ready[64];
__device__ __align__(128) uint32_t g_sig[N_OWN * 128];

#define TL(i) ((void)0)
#define TLV(i, v) ((void)0)
#define TLA(k) ((void)0)

__device__ __forceinline__ uint32_t smem_u32(const void* p) { return (uint32_t)__cvta_generic_to_shared(p); }
__device__ __forceinline__ void mbar_init(uint32_t bar, uint32_t cnt) {
    asm volatile("mbarrier.init.shared::cta.b64 [%0], %1;" ::"r"(bar), "r"(cnt) : "memory");
}
__device__ __forceinline__ void mbar_expect_tx(uint32_t bar, uint32_t bytes) {
    asm volatile("mbarrier.arrive.expect_tx.shared::cta.b64 _, [%0], %1;" ::"r"(bar), "r"(bytes) : "memory");
}
__device__ __forceinline__ void mbar_arrive(uint32_t bar) {
    asm volatile("mbarrier.arrive.shared::cta.b64 _, [%0];" ::"r"(bar) : "memory");
}
__device__ __forceinline__ bool mbar_try(uint32_t bar, uint32_t parity) {
    uint32_t ok;
    asm volatile("{\n.reg .pred p;\nmbarrier.try_wait.parity.shared::cta.b64 p, [%1], %2;\nselp.u32 %0, 1, 0, p;\n}"
                 : "=r"(ok) : "r"(bar), "r"(parity) : "memory");
    return ok != 0;
}
__device__ __forceinline__ void mbar_wait(uint32_t bar, uint32_t parity) {
    uint32_t spins = 0;
    while (!mbar_try(bar, parity)) {
        if (++spins > (1u << 26)) __trap();
    }
}
__device__ __forceinline__ void bulk_g2s(uint32_t dst, const void* src, uint32_t bytes, uint32_t bar) {
    asm volatile("cp.async.bulk.shared::cluster.global.mbarrier::complete_tx::bytes [%0], [%1], %2, [%3];"
                 ::"r"(dst), "l"(src), "r"(bytes), "r"(bar) : "memory");
}
__device__ __forceinline__ void bulk_g2s_hint(uint32_t dst, const void* src, uint32_t bytes, uint32_t bar, uint64_t pol) {
    asm volatile("cp.async.bulk.shared::cluster.global.mbarrier::complete_tx::bytes.L2::cache_hint [%0], [%1], %2, [%3], %4;"
                 ::"r"(dst), "l"(src), "r"(bytes), "r"(bar), "l"(pol) : "memory");
}
__device__ __forceinline__ void tma_2d(uint32_t dst, const CUtensorMap* map, int c0, int c1, uint32_t bar) {
    asm volatile("cp.async.bulk.tensor.2d.shared::cluster.global.mbarrier::complete_tx::bytes [%0], [%1, {%3, %4}], [%2];"
                 ::"r"(dst), "l"(map), "r"(bar), "r"(c0), "r"(c1) : "memory");
}
__device__ __forceinline__ unsigned atom_add_relaxed(unsigned* p, unsigned v) {
    unsigned o;
    asm volatile("atom.relaxed.gpu.global.add.u32 %0, [%1], %2;" : "=r"(o) : "l"(p), "r"(v) : "memory");
    return o;
}
template <int OFF = 0>
__device__ __forceinline__ uint32_t ld_rlx(const void* p) {
    uint32_t v;
    asm volatile("ld.relaxed.gpu.global.u32 %0, [%1+%2];" : "=r"(v) : "l"(p), "n"(OFF) : "memory");
    return v;
}
__device__ __forceinline__ uint32_t ld_acq(const void* p) {
    uint32_t v;
    asm volatile("ld.acquire.gpu.global.u32 %0, [%1];" : "=r"(v) : "l"(p) : "memory");
    return v;
}
template <int OFF = 0>
__device__ __forceinline__ uint2 ld_rlx2(const void* p) {
    uint2 v;
    asm volatile("ld.relaxed.gpu.global.v2.u32 {%0,%1}, [%2+%3];" : "=r"(v.x), "=r"(v.y) : "l"(p), "n"(OFF) : "memory");
    return v;
}
template <int OFF = 0>
__device__ __forceinline__ uint4 ld_rlx4(const void* p) {
    uint4 v;
    asm volatile("ld.relaxed.gpu.global.v4.u32 {%0,%1,%2,%3}, [%4+%5];" : "=r"(v.x), "=r"(v.y), "=r"(v.z), "=r"(v.w) : "l"(p), "n"(OFF) : "memory");
    return v;
}
__device__ __forceinline__ void st_rlx(void* p, uint32_t v) {
    asm volatile("st.relaxed.gpu.global.u32 [%0], %1;" ::"l"(p), "r"(v) : "memory");
}
template <int OFF = 0>
__device__ __forceinline__ void st_rlx2(void* p, uint32_t a, uint32_t b) {
    asm volatile("st.relaxed.gpu.global.v2.u32 [%0+%3], {%1,%2};" ::"l"(p), "r"(a), "r"(b), "n"(OFF) : "memory");
}
__device__ __forceinline__ void st_rlx4(void* p, uint32_t a, uint32_t b, uint32_t c, uint32_t d) {
    asm volatile("st.relaxed.gpu.global.v4.u32 [%0], {%1,%2,%3,%4};" ::"l"(p), "r"(a), "r"(b), "r"(c), "r"(d) : "memory");
}
template <int N, class F>
__device__ __forceinline__ void static_for(F&& f) {
    if constexpr (N > 0) { static_for<N - 1>(f); f(std::integral_constant<int, N - 1>{}); }
}
__device__ __forceinline__ uint32_t nzf(float v) { const uint32_t u = __float_as_uint(v); return u ? u : 0x80000000u; }
__device__ __forceinline__ uint32_t nzb(uint32_t u) { return u ? u : 0x00008000u; }
__device__ __forceinline__ bool ok4(const uint4& v) { return v.x && v.y && v.z && v.w; }
__device__ __forceinline__ void spin_guard(uint32_t& spins) { if (++spins > (1u << 23)) __trap(); }
__device__ __forceinline__ uint32_t pack_bf2(float lo, float hi) {
    const __nv_bfloat162 v = __floats2bfloat162_rn(lo, hi);
    return *reinterpret_cast<const uint32_t*>(&v);
}
__device__ __forceinline__ void cons_bar() { asm volatile("bar.sync 1, 256;" ::: "memory"); }
__device__ __forceinline__ void ldsm4(uint32_t (&r)[4], uint32_t addr) {
    asm volatile("ldmatrix.sync.aligned.m8n8.x4.shared.b16 {%0,%1,%2,%3}, [%4];"
                 : "=r"(r[0]), "=r"(r[1]), "=r"(r[2]), "=r"(r[3]) : "r"(addr) : "memory");
}
__device__ __forceinline__ void ldsm4t(uint32_t (&r)[4], uint32_t addr) {
    asm volatile("ldmatrix.sync.aligned.m8n8.x4.trans.shared.b16 {%0,%1,%2,%3}, [%4];"
                 : "=r"(r[0]), "=r"(r[1]), "=r"(r[2]), "=r"(r[3]) : "r"(addr) : "memory");
}
__device__ __forceinline__ void mma16816(float (&c)[4], const uint32_t (&a)[4], uint32_t b0, uint32_t b1) {
    asm volatile("mma.sync.aligned.m16n8k16.row.col.f32.bf16.bf16.f32 {%0,%1,%2,%3}, {%4,%5,%6,%7}, {%8,%9}, {%0,%1,%2,%3};"
                 : "+f"(c[0]), "+f"(c[1]), "+f"(c[2]), "+f"(c[3])
                 : "r"(a[0]), "r"(a[1]), "r"(a[2]), "r"(a[3]), "r"(b0), "r"(b1));
}
__device__ __forceinline__ float bf16r(float x) { return __uint_as_float(pack_bf2(0.f, x) & 0xffff0000u); }
__device__ __forceinline__ float bf_lo(uint32_t u) { return __uint_as_float(u << 16); }
__device__ __forceinline__ float bf_hi(uint32_t u) { return __uint_as_float(u & 0xffff0000u); }
__device__ __forceinline__ float ex2(float x) { float y; asm("ex2.approx.ftz.f32 %0, %1;" : "=f"(y) : "f"(x)); return y; }
__device__ __forceinline__ float warp_sum(float v) {
#pragma unroll
    for (int o = 16; o > 0; o >>= 1) v += __shfl_xor_sync(0xffffffffu, v, o);
    return v;
}
__device__ __forceinline__ float warp_max(float v) {
#pragma unroll
    for (int o = 16; o > 0; o >>= 1) v = fmaxf(v, __shfl_xor_sync(0xffffffffu, v, o));
    return v;
}
__device__ __forceinline__ uint32_t lds32(uint32_t a) { uint32_t v; asm volatile("ld.shared.u32 %0, [%1];" : "=r"(v) : "r"(a) : "memory"); return v; }

__device__ __forceinline__ void warp_layernorm(uint32_t (&w)[9]) {
    const float k = bf_lo(__shfl_sync(0xffffffffu, w[0], 0));
    float s0 = 0.f, s1 = 0.f, q0 = 0.f, q1 = 0.f;
#pragma unroll
    for (int i = 0; i < 9; i++) {
        const float a = bf_lo(w[i]) - k, b = bf_hi(w[i]) - k;
        s0 += a; s1 += b; q0 = fmaf(a, a, q0); q1 = fmaf(b, b, q1);
    }
    float s = s0 + s1, q = q0 + q1;
#pragma unroll
    for (int o = 16; o > 0; o >>= 1) { s += __shfl_xor_sync(0xffffffffu, s, o); q += __shfl_xor_sync(0xffffffffu, q, o); }
    const float dm = s * (1.0f / DM);
    const uint32_t mv = pack_bf2(k + dm, fmaxf(fmaf(-dm, dm, q * (1.0f / DM)), 0.f));
    const float m = bf_lo(mv);
    float sd, rs;
    asm("sqrt.approx.ftz.f32 %0, %1;" : "=f"(sd) : "f"(bf16r(bf_hi(mv) + LN_EPS)));
    asm("rcp.approx.ftz.f32 %0, %1;" : "=f"(rs) : "f"(bf16r(sd)));
#pragma unroll
    for (int i = 0; i < 9; i++) {
        const uint32_t d = pack_bf2(bf_lo(w[i]) - m, bf_hi(w[i]) - m);
        w[i] = pack_bf2(bf_lo(d) * rs, bf_hi(d) * rs);
    }
}

__device__ __forceinline__ void pool_item(unsigned idx, int& bh, int& tile0, int& nt, int& slot) {
    const int lev = idx >> 7;
    bh = idx & 127;
    slot = lev + 1;
    nt = (int)(LEV_SIZE >> (5 * lev)) & 31;
    tile0 = L0 + ((int)(LEV_START >> (5 * lev)) & 31);
}

__device__ __forceinline__ void rows_load(uint32_t (&a)[5][4], uint32_t wrows, int warp, int lane) {
    const uint32_t arow = wrows + ((lane & 7) + 8 * (lane >> 4)) * W_PITCH + ((lane >> 3) & 1) * 16 + warp * 32;
#pragma unroll
    for (int i = 0; i < 4; i++) ldsm4t(a[i], arow + i * 256);
    ldsm4t(a[4], arow + (warp < 4 ? 4 * 256 : 0));
}
__device__ __forceinline__ void rows_mma(float (&acc)[5][4], const uint32_t (&a)[5][4], uint32_t act, int lane) {
    uint32_t b0 = 0, b1 = 0;
    if (lane < 16) { b0 = lds32(act); b1 = lds32(act + 16); }
#pragma unroll
    for (int i = 0; i < 5; i++) mma16816(acc[i], a[i], b0, b1);
}
template <int NSRC>
__device__ __forceinline__ void rows_store(const float (&acc)[5][4], float* dst, int src, int warp, int lane) {
    const int g = lane >> 2, c = lane & 3;
    float* d = dst + (warp * NSRC + src) * 64 + g * 4 + 2 * c;
    if (c < 2) {
        static_for<5>([&](auto I) {
            constexpr int i = decltype(I)::value;
            if (i < 4 || warp < 4) {
                st_rlx2<i * 8 * NSRC * 256>(d, nzf(acc[i][0]), nzf(acc[i][1]));
                st_rlx2<i * 8 * NSRC * 256 + 128>(d, nzf(acc[i][2]), nzf(acc[i][3]));
            }
        });
    }
}
template <int R>
__device__ __forceinline__ void wait_signal(const uint32_t* sig, int lane, uint32_t tag) {
    uint32_t spins = 0;
    while (true) {
        bool ok = true;
        static_for<R>([&](auto I) { constexpr int r = decltype(I)::value; ok = (ld_rlx<r * 128>(sig + lane) == tag) && ok; });
        if (__all_sync(0xffffffffu, ok)) break;
        spin_guard(spins);
    }
}
template <int R>
__device__ __forceinline__ void owner_gather(const float* src, float* red, int warp, int tid, const uint32_t* sig, uint32_t tag, bool try_first) {
    uint4 v[R];
    uint32_t pending = (1u << R) - 1, spins = 0;
    const float* p = src + tid * 4;
    if (!try_first) wait_signal<R / 2>(sig, tid & 31, tag);
    while (true) {
        static_for<R>([&](auto I) { constexpr int r = decltype(I)::value; if (pending >> r & 1) v[r] = ld_rlx4<r * NCONS * 16>(p); });
#pragma unroll
        for (int r = 0; r < R; r++)
            if (ok4(v[r])) pending &= ~(1u << r);
        if (!__any_sync(0xffffffffu, pending)) break;
        if (try_first) { wait_signal<R / 2>(sig, tid & 31, tag); try_first = false; }
        spin_guard(spins);
    }
    float4 a = make_float4(__uint_as_float(v[0].x), __uint_as_float(v[0].y), __uint_as_float(v[0].z), __uint_as_float(v[0].w));
#pragma unroll
    for (int r = 1; r < R; r++) {
        a.x += __uint_as_float(v[r].x); a.y += __uint_as_float(v[r].y); a.z += __uint_as_float(v[r].z); a.w += __uint_as_float(v[r].w);
    }
    __syncwarp();
    const bool hi = tid & 16;
    const float u0 = (hi ? a.z : a.x) + __shfl_xor_sync(0xffffffffu, hi ? a.x : a.z, 16);
    const float u1 = (hi ? a.w : a.y) + __shfl_xor_sync(0xffffffffu, hi ? a.y : a.w, 16);
    float* r = red + warp * 64 + (hi ? 32 : 0) + (tid & 15);
    r[0] = u0; r[16] = u1;
}
__device__ __forceinline__ float2 owner_sum(const float* red, int pr, int b) {
    float2 v[8];
#pragma unroll
    for (int w8 = 0; w8 < 8; w8++) v[w8] = *reinterpret_cast<const float2*>(red + w8 * 64 + b * 16 + 2 * pr);
    return make_float2(((v[0].x + v[1].x) + (v[2].x + v[3].x)) + ((v[4].x + v[5].x) + (v[6].x + v[7].x)),
                       ((v[0].y + v[1].y) + (v[2].y + v[3].y)) + ((v[4].y + v[5].y) + (v[6].y + v[7].y)));
}
__device__ __forceinline__ void wait_ready(int lane, uint32_t tag) {
    uint32_t spins = 0;
    while (true) {
        const bool a = ld_acq(g_ready + lane) == tag, b = lane >= N_OWN - 32 || ld_acq(g_ready + 32 + lane) == tag;
        if (__all_sync(0xffffffffu, a && b)) break;
        spin_guard(spins);
    }
}

__global__ void __launch_bounds__(NTHREADS, 1)
decode_layer_kernel(const __nv_bfloat16* __restrict__ x, const __nv_bfloat16* __restrict__ kc,
                    const __nv_bfloat16* __restrict__ vc, const __nv_bfloat16* __restrict__ wq,
                    const __nv_bfloat16* __restrict__ wo, const __nv_bfloat16* __restrict__ wd,
                    __nv_bfloat16* __restrict__ out,
                    const __grid_constant__ CUtensorMap map_g, const __grid_constant__ CUtensorMap map_u) {
    extern __shared__ __align__(1024) unsigned char smem[];
    const uint32_t sb = smem_u32(smem);
    const int tid = threadIdx.x, warp = tid >> 5, lane = tid & 31;
    const int cta = blockIdx.x;
    const bool is_ffn = cta < N_FFN;
    const bool is_wo = cta >= N_FFN && cta < NBH;
    const uint32_t bars = sb + OFF_BAR;

    if (warp == 8) {
        int u = 0;
        uint32_t tag = 0;
        if (lane == 0) {
            TL(0);
            TLA(0);
            tag = ld_rlx(&g_epoch.v) + 1;
#pragma unroll
            for (int i = 0; i < 6; i++) { mbar_init(bars + (BAR_FULL + i) * 8, 1); mbar_init(bars + (BAR_EMPTY + i) * 8, 8); }
#pragma unroll
            for (int i = 0; i < 8; i++) mbar_init(bars + (BAR_DESC + i) * 8, 1);
#pragma unroll
            for (int i = 0; i < 12; i++) mbar_init(bars + (BAR_W + i) * 8, 1);
            asm volatile("fence.mbarrier_init.release.cluster;" ::: "memory");
            asm volatile("fence.proxy.async.shared::cta;" ::: "memory");
        }
        __syncwarp();
        asm volatile("bar.arrive 2, 320;" ::: "memory");
        if (lane == 0) {
            uint64_t pol;
            asm volatile("createpolicy.fractional.L2::evict_first.b64 %0, 1.0;" : "=l"(pol));
            int bh, tile0, nt, slot;
            unsigned idx = 0;
            if (cta < NBH) { bh = cta; tile0 = 0; nt = L0; slot = 0; }
            else { idx = cta - NBH; pool_item(idx, bh, tile0, nt, slot); }
            int n = 0;
            int s = 0; uint32_t ph = 1;
            int sa = 0; uint32_t pa = 0;
            int acked = 0;
            bool zeroed = is_ffn;
            while (true) {
                const char* kp = (const char*)kc + ((size_t)bh * SK + (size_t)tile0 * TILE) * (DH * 2);
                const char* vp = (const char*)vc + ((size_t)bh * SK + (size_t)tile0 * TILE) * (DH * 2);
                if (n > 0) {
                    const uint32_t dslot = n & 7;
                    *reinterpret_cast<int4*>(smem + OFF_DESC + dslot * 16) = make_int4(bh, nt, slot, 0);
                    mbar_expect_tx(bars + (BAR_DESC + dslot) * 8, 256);
                    bulk_g2s(sb + OFF_Q + dslot * 256, g_q + bh * 64, 256, bars + (BAR_DESC + dslot) * 8);
                }
                auto issue = [&](int t) {
                    const int nf = u < NF_START_SLOTS ? NF_START : (idx >= (unsigned)T_END ? NF_END : NF);
                    while (u - acked >= nf) {
                        mbar_wait(bars + (BAR_FULL + sa) * 8, pa);
                        acked++;
                        if (++sa == 2 * NPAIR) { sa = 0; pa ^= 1; }
                    }
                    mbar_wait(bars + (BAR_EMPTY + s) * 8, ph);
                    mbar_expect_tx(bars + (BAR_FULL + s) * 8, TILE_BYTES);
                    bulk_g2s_hint(sb + s * TILE_BYTES, ((t & 1) ? vp : kp) + (size_t)(t >> 1) * TILE_BYTES, TILE_BYTES,
                                  bars + (BAR_FULL + s) * 8, pol);
                    u++;
                    if (++s == 2 * NPAIR) { s = 0; ph ^= 1; }
                };
#pragma unroll 1
                for (int t = 0; t < 2 * nt - CLAIM_AHEAD; t++) {
                    issue(t);
                    if (u == 1) {
                        *reinterpret_cast<volatile uint32_t*>(smem + OFF_TAG) = tag;
                        if (is_ffn) {
                            asm volatile("prefetch.tensormap [%0];" ::"l"(&map_g) : "memory");
                            asm volatile("prefetch.tensormap [%0];" ::"l"(&map_u) : "memory");
                        }
                    }
                }
                unsigned next = NPOOL;
                {
                    const uint32_t more = !(is_wo && idx >= (unsigned)T_WO);
                    asm volatile("{\n.reg .pred p;\nsetp.ne.u32 p, %2, 0;\n@p atom.relaxed.gpu.global.inc.u32 %0, [%1], 0x7fffffff;\n}"
                                 : "+r"(next) : "l"(&g_pool.v), "r"(more) : "memory");
                }
#pragma unroll
                for (int t = 2 * nt - CLAIM_AHEAD; t < 2 * nt; t++) issue(t);
                next += GRID - NBH;
                n++;
                idx = next;
                if (!zeroed && idx >= (unsigned)T_ZERO) { mbar_arrive(bars + BAR_ZERO * 8); zeroed = true; }
                if (idx >= NPOOL) break;
                pool_item(idx, bh, tile0, nt, slot);
            }
            *reinterpret_cast<int4*>(smem + OFF_DESC + (n & 7) * 16) = make_int4(0, 0, 0, 0);
            mbar_arrive(bars + (BAR_DESC + (n & 7)) * 8);
            TL(2);
            if (is_ffn && HOLD > 0) {
                const long long t0 = clock64(), d = (long long)HOLD * max(0, GRID - NH - (int)(idx - NPOOL)) + CFG_HOLD0;
                while (clock64() - t0 < d) {}
            }
            TLV(30, n);
            TLV(31, u >> 1);
        }
        u = __shfl_sync(0xffffffffu, u, 0);
        if (is_ffn || is_wo) {
            const int npieces = is_ffn ? 11 : 8;
            const int nfw = is_ffn ? NFW : NFWO;
#pragma unroll 1
            for (int i = 0; i < npieces; i++) {
                const int r = is_ffn ? (i >> 2) : i / 3;
                const int j = is_ffn ? (i & 3) : i - 3 * r;
                const int pu = (u >> 1) + r;
                const int p = pu % NPAIR;
                const uint32_t dst = sb + 2 * p * TILE_BYTES;
                const uint32_t wb = bars + (BAR_W + i) * 8;
                const bool tensor = is_ffn && r < 2;
                if (lane == 0) {
                    if (i >= nfw) mbar_wait(bars + (BAR_W + i - nfw) * 8, 0);
                    else { const int v = u - 2 + (2 * i) / nfw; mbar_wait(bars + (BAR_FULL + v % (2 * NPAIR)) * 8, (v / (2 * NPAIR)) & 1); }
                    if (j == 0) {
                        const uint32_t pe = ((pu / NPAIR) & 1) ^ 1;
                        mbar_wait(bars + (BAR_EMPTY + 2 * p) * 8, pe);
                        mbar_wait(bars + (BAR_EMPTY + 2 * p + 1) * 8, pe);
                    }
                    mbar_expect_tx(wb, tensor ? GU_BOX_BYTES : 16 * DM * 2);
                    if (tensor) tma_2d(dst + j * GU_BOX_BYTES, r == 0 ? &map_g : &map_u, cta * FC, j * GU_BOXROWS, wb);
                }
                __syncwarp();
                if (!tensor && lane < 16) {
                    const __nv_bfloat16* src = is_ffn ? wd + (size_t)(cta * FC + j * 16 + lane) * DM
                                                      : wo + (size_t)((cta - N_FFN) * DH + i * 16 + lane) * DM;
                    bulk_g2s(dst + (j * 16 + lane) * W_PITCH, src, DM * 2, wb);
                }
            }
            if (lane == 0) TL(3);
        }
        if (lane == 0) TLA(1);
        if (lane == 0 && atom_add_relaxed(&g_done.v, 1) == GRID - 1) { g_pool.v = 0; g_done.v = 0; g_epoch.v = tag; }
        return;
    }
    if (warp == 9) {
        asm volatile("bar.sync 2, 320;" ::: "memory");
        int bh = cta, tile0, nt = L0, slot = 0;
        if (cta >= NBH) pool_item(cta - NBH, bh, tile0, nt, slot);
        uint2 qv;
        uint32_t spins = 0;
        do { qv = ld_rlx2(g_q + bh * 64 + 2 * lane); spin_guard(spins); } while (!(qv.x && qv.y));
        *reinterpret_cast<uint2*>(smem + OFF_Q + 8 * lane) = qv;
        __syncwarp();
        if (lane == 0) {
            TL(1);
            *reinterpret_cast<int4*>(smem + OFF_DESC) = make_int4(bh, nt, slot, 0);
            mbar_arrive(bars + BAR_DESC * 8);
        }
        if (!is_ffn) {
            const int own = cta - N_FFN;
            mbar_wait(bars + BAR_ZERO * 8, 0);
#pragma unroll 4
            for (int i = lane; i < NH * 16; i += 32) st_rlx4(g_att + own * NH * 64 + i * 4, 0, 0, 0, 0);
#pragma unroll 4
            for (int i = lane; i < N_FFN * 16; i += 32) st_rlx4(g_y + own * N_FFN * 64 + i * 4, 0, 0, 0, 0);
            for (int i = lane; i < H_REP * NB * 2; i += 32) st_rlx4(g_h + (i >> 1) * (DM / 2) + own * 8 + (i & 1) * 4, 0, 0, 0, 0);
            asm volatile("fence.acq_rel.gpu;" ::: "memory");
            __syncwarp();
            if (lane == 0) {
                asm volatile("fence.acq_rel.gpu;" ::: "memory");
                st_rlx(g_ready + own, *reinterpret_cast<volatile uint32_t*>(smem + OFF_TAG));
                TL(14);
            }
        }
        return;
    }

    const int g = lane >> 2, c = lane & 3;
    if (cta < NBH) {
        uint4 w[9];
        const __nv_bfloat16* wp = wq + (size_t)(tid >> 2) * (NH * DH) + cta * 32 + (tid & 3) * 8;
#pragma unroll
        for (int i = 0; i < 9; i++)
            asm volatile("ld.global.nc.L1::no_allocate.v4.u32 {%0,%1,%2,%3}, [%4];"
                         : "=r"(w[i].x), "=r"(w[i].y), "=r"(w[i].z), "=r"(w[i].w) : "l"(wp + (size_t)i * 64 * (NH * DH)));
        float* xn = reinterpret_cast<float*>(smem + OFF_XN);
        if (warp < 4) {
            uint32_t v[9];
            const uint32_t* xp = reinterpret_cast<const uint32_t*>(x + warp * DM);
#pragma unroll
            for (int i = 0; i < 9; i++) v[i] = __ldg(xp + lane + 32 * i);
            warp_layernorm(v);
#pragma unroll
            for (int i = 0; i < 9; i++) {
                xn[(2 * (lane + 32 * i)) * 4 + warp] = bf_lo(v[i]);
                xn[(2 * (lane + 32 * i) + 1) * 4 + warp] = bf_hi(v[i]);
            }
        }
        cons_bar();
        float a[32];
#pragma unroll
        for (int i = 0; i < 32; i++) a[i] = 0.f;
#pragma unroll
        for (int i = 0; i < 9; i++) {
            const float4 xv = *reinterpret_cast<const float4*>(xn + ((tid >> 2) + 64 * i) * 4);
            const float wf[8] = {bf_lo(w[i].x), bf_hi(w[i].x), bf_lo(w[i].y), bf_hi(w[i].y),
                                 bf_lo(w[i].z), bf_hi(w[i].z), bf_lo(w[i].w), bf_hi(w[i].w)};
#pragma unroll
            for (int e = 0; e < 8; e++) {
                a[e] = fmaf(xv.x, wf[e], a[e]);
                a[8 + e] = fmaf(xv.y, wf[e], a[8 + e]);
                a[16 + e] = fmaf(xv.z, wf[e], a[16 + e]);
                a[24 + e] = fmaf(xv.w, wf[e], a[24 + e]);
            }
        }
        {
            const bool b4 = lane & 16, b3 = lane & 8, b2 = lane & 4;
#pragma unroll
            for (int i = 0; i < 16; i++) { const float s = b4 ? a[i] : a[i + 16], k = b4 ? a[i + 16] : a[i]; a[i] = k + __shfl_xor_sync(0xffffffffu, s, 16); }
#pragma unroll
            for (int i = 0; i < 8; i++) { const float s = b3 ? a[i] : a[i + 8], k = b3 ? a[i + 8] : a[i]; a[i] = k + __shfl_xor_sync(0xffffffffu, s, 8); }
#pragma unroll
            for (int i = 0; i < 4; i++) { const float s = b2 ? a[i] : a[i + 4], k = b2 ? a[i + 4] : a[i]; a[i] = k + __shfl_xor_sync(0xffffffffu, s, 4); }
            float* qred = reinterpret_cast<float*>(smem + OFF_QRED);
            const int b = (lane >> 3) & 3;
            *reinterpret_cast<float4*>(qred + warp * 128 + b * 32 + (lane & 3) * 8 + (b2 ? 4 : 0)) = make_float4(a[0], a[1], a[2], a[3]);
        }
        cons_bar();
        if (tid < 64) {
            const float2* qred = reinterpret_cast<const float2*>(smem + OFF_QRED);
            float s0 = 0.f, s1 = 0.f;
#pragma unroll
            for (int w8 = 0; w8 < 8; w8++) { const float2 v = qred[w8 * 64 + tid]; s0 += v.x; s1 += v.y; }
            st_rlx(g_q + ((tid >> 4) * NH + (cta >> 2)) * 64 + (cta & 3) * 16 + (tid & 15), nzb(pack_bf2(s0, s1)));
            if (tid == 0) TL(4);
        }
    }
    asm volatile("bar.sync 2, 320;" ::: "memory");

    uint32_t offK[4], offV[4];
    {
        const int i = lane & 7;
        const uint32_t rk = (16 * warp + i + 8 * ((lane >> 3) & 1)) * 256, xk = (lane >> 4) ^ i;
        const uint32_t rv = (16 * warp + i + 8 * (lane >> 4)) * 256, xv = ((lane >> 3) & 1) ^ i;
#pragma unroll
        for (int j = 0; j < 4; j++) { offK[j] = rk + (((2 * j) ^ xk) << 4); offV[j] = rv + (((2 * j) ^ xv) << 4) + TILE_BYTES; }
    }
    const bool valid = (c == (g >> 1));
    const bool odd = g & 1;
    int p = 0, it = 0;
    uint32_t ph = 0;
    for (int n = 0;; n++) {
        mbar_wait(bars + (BAR_DESC + (n & 7)) * 8, (n >> 3) & 1);
        const int4 d = *reinterpret_cast<const int4*>(smem + OFF_DESC + (n & 7) * 16);
        const int nt = d.y;
        if (nt == 0) break;
        uint32_t qf[8][2];
        {
            const uint32_t qa = sb + OFF_Q + (n & 7) * 256 + c * 4;
            bool ok = true;
#pragma unroll
            for (int j = 0; j < 8; j++) {
                qf[j][0] = lds32(qa + (((2 * j) ^ g) << 4)); qf[j][1] = lds32(qa + (((2 * j + 1) ^ g) << 4));
                ok = ok && qf[j][0] && qf[j][1];
            }
            uint32_t spins = 0;
            while (!ok) {
                const uint32_t* qg = g_q + d.x * 64 + c;
                ok = true;
#pragma unroll
                for (int j = 0; j < 8; j++) {
                    qf[j][0] = ld_rlx(qg + (((2 * j) ^ g) << 2)); qf[j][1] = ld_rlx(qg + (((2 * j + 1) ^ g) << 2));
                    ok = ok && qf[j][0] && qf[j][1];
                }
                spin_guard(spins);
            }
            __syncwarp();
        }
        float acc[8][4];
#pragma unroll
        for (int j = 0; j < 8; j++) { acc[j][0] = acc[j][1] = acc[j][2] = acc[j][3] = 0.f; }
        float m = -INFINITY, l = 0.f;
#pragma unroll 1
        for (int t = 0; t < nt; t++) {
            const uint32_t base = sb + 2 * p * TILE_BYTES;
            mbar_wait(bars + (BAR_FULL + 2 * p) * 8, ph);
            float sa[4] = {0.f, 0.f, 0.f, 0.f}, sc[4] = {0.f, 0.f, 0.f, 0.f};
            {
                uint32_t a[8][4];
#pragma unroll
                for (int j = 0; j < 8; j++) ldsm4(a[j], base + offK[j & 3] + (j >> 2) * 128);
#pragma unroll
                for (int j = 0; j < 8; j += 2) { mma16816(sa, a[j], qf[j][0], qf[j][1]); mma16816(sc, a[j + 1], qf[j + 1][0], qf[j + 1][1]); }
            }
            __syncwarp();
            if (lane == 0) mbar_arrive(bars + (BAR_EMPTY + 2 * p) * 8);
            float s0 = odd ? sa[1] + sc[1] : sa[0] + sc[0];
            float s1 = odd ? sa[3] + sc[3] : sa[2] + sc[2];
            {
                const uint32_t r1 = pack_bf2(s0, s1);
                const uint32_t r2 = pack_bf2(bf_lo(r1) * SM_SCALE, bf_hi(r1) * SM_SCALE);
                s0 = valid ? bf_lo(r2) : -INFINITY;
                s1 = valid ? bf_hi(r2) : -INFINITY;
            }
            const float smax = fmaxf(s0, s1);
            if (__any_sync(0xffffffffu, smax > m)) {
                const float mn = fmaxf(m, warp_max(smax));
                const float corr = ex2((m - mn) * LOG2E);
                m = mn;
                l *= corr;
#pragma unroll
                for (int j = 0; j < 8; j++) { acc[j][0] *= corr; acc[j][1] *= corr; acc[j][2] *= corr; acc[j][3] *= corr; }
            }
            const float p0 = ex2((s0 - m) * LOG2E), p1 = ex2((s1 - m) * LOG2E);
            l += p0 + p1;
            const uint32_t pp = pack_bf2(p0, p1);
            const uint32_t pb0 = odd ? pp << 16 : pp & 0xffffu;
            const uint32_t pb1 = odd ? pp & 0xffff0000u : pp >> 16;
            mbar_wait(bars + (BAR_FULL + 2 * p + 1) * 8, ph);
            {
                uint32_t a[8][4];
#pragma unroll
                for (int j = 0; j < 8; j++) ldsm4t(a[j], base + offV[j & 3] + (j >> 2) * 128);
#pragma unroll
                for (int j = 0; j < 8; j++) mma16816(acc[j], a[j], pb0, pb1);
            }
            __syncwarp();
            if (lane == 0) mbar_arrive(bars + (BAR_EMPTY + 2 * p + 1) * 8);
            it++;
            if (++p == NPAIR) { p = 0; ph ^= 1; }
        }
        float ev[8], od[8];
#pragma unroll
        for (int j = 0; j < 8; j++) { ev[j] = acc[j][0] + acc[j][3]; od[j] = acc[j][1] + acc[j][2]; }
#pragma unroll
        for (int j = 0; j < 8; j += 2) { ev[j] += __shfl_xor_sync(0xffffffffu, ev[j + 1], 1); od[j] += __shfl_xor_sync(0xffffffffu, od[j + 1], 1); }
#pragma unroll
        for (int j = 0; j < 8; j += 4) { ev[j] += __shfl_xor_sync(0xffffffffu, ev[j + 2], 2); od[j] += __shfl_xor_sync(0xffffffffu, od[j + 2], 2); }
        l = warp_sum(l);
        float* red = reinterpret_cast<float*>(smem + OFF_RED) + (n & 1) * 8 * PART_STRIDE;
        {
            float* r = red + warp * PART_STRIDE;
            r[16 * c + g] = ev[0]; r[16 * c + 8 + g] = od[0];
            r[64 + 16 * c + g] = ev[4]; r[64 + 16 * c + 8 + g] = od[4];
            if (lane == 0) { r[128] = m; r[129] = l; }
        }
        cons_bar();
        if (warp == 7) {
            float M = red[128];
#pragma unroll
            for (int w8 = 1; w8 < 8; w8++) M = fmaxf(M, red[w8 * PART_STRIDE + 128]);
            float4 o = make_float4(0.f, 0.f, 0.f, 0.f);
            float L = 0.f;
#pragma unroll
            for (int w8 = 0; w8 < 8; w8++) {
                const float f = ex2((red[w8 * PART_STRIDE + 128] - M) * LOG2E);
                const float4 v = *reinterpret_cast<const float4*>(red + w8 * PART_STRIDE + 4 * lane);
                o.x = fmaf(f, v.x, o.x); o.y = fmaf(f, v.y, o.y); o.z = fmaf(f, v.z, o.z); o.w = fmaf(f, v.w, o.w);
                L = fmaf(f, red[w8 * PART_STRIDE + 129], L);
            }
            float* gp = g_part + (size_t)(d.x * NSLOT + d.z) * PART_STRIDE;
            st_rlx4(gp + 4 * lane, nzf(o.x), nzf(o.y), nzf(o.z), nzf(o.w));
            if (lane < 2) st_rlx4(gp + 128 + 4 * lane, nzf(M), nzf(L), 1u, 1u);
            if (lane == 0) TL(6);
        }
    }

    const uint32_t tag = *reinterpret_cast<volatile uint32_t*>(smem + OFF_TAG);
    const uint32_t reg0 = sb + 2 * ((it + 0) % NPAIR) * TILE_BYTES;
    const uint32_t reg1 = sb + 2 * ((it + 1) % NPAIR) * TILE_BYTES;
    const uint32_t reg2 = sb + 2 * ((it + 2) % NPAIR) * TILE_BYTES;
    if (!is_ffn) {
        const int own = cta - N_FFN;
        const int ob = (tid >> 3) & 3, opr = tid & 7;
        const uint32_t xw = __ldg(reinterpret_cast<const uint32_t*>(x + ob * DM + own * 16 + 2 * opr));
        wait_ready(lane, tag);
        if (is_wo) {
            const int h = own;
            const int b = tid >> 6, dp = tid & 63;
            uint32_t wf[WO_PRE][5][4];
#pragma unroll
            for (int ks = 0; ks < WO_PRE; ks++) {
                mbar_wait(bars + (BAR_W + ks) * 8, 0);
                rows_load(wf[ks], (ks < 3 ? reg0 : ks < 6 ? reg1 : reg2) + (ks % 3) * 16 * W_PITCH, warp, lane);
            }
            if (tid == 0) TL(17);
            float* gp = g_part + (size_t)((b * NH + h) * NSLOT) * PART_STRIDE;
            {
                uint2 ml = make_uint2(1, 1), ov[NSLOT];
                uint32_t pending = (2u << NSLOT) - 1, spins = 0;
                const float* pml = gp + lane * PART_STRIDE + 128;
                const float* pov = gp + 2 * dp;
                while (pending) {
                    if ((pending >> NSLOT & 1) && lane < NSLOT) ml = ld_rlx2(pml);
                    static_for<NSLOT>([&](auto I) { constexpr int i = decltype(I)::value; if (pending >> i & 1) ov[i] = ld_rlx2<i * PART_STRIDE * 4>(pov); });
                    if (ml.x && ml.y) pending &= ~(1u << NSLOT);
#pragma unroll
                    for (int i = 0; i < NSLOT; i++)
                        if (ov[i].x && ov[i].y) pending &= ~(1u << i);
                    spin_guard(spins);
                }
                __syncwarp();
                if (tid == 0) TL(7);
                const float mi = lane < NSLOT ? __uint_as_float(ml.x) : -INFINITY;
                float M = mi;
#pragma unroll
                for (int o = 8; o > 0; o >>= 1) M = fmaxf(M, __shfl_xor_sync(0xffffffffu, M, o));
                M = __shfl_sync(0xffffffffu, M, 0);
                const float f = ex2((mi - M) * LOG2E);
                float L = 0.f, o0 = 0.f, o1 = 0.f;
#pragma unroll
                for (int i = 0; i < NSLOT; i++) {
                    const float fi = __shfl_sync(0xffffffffu, f, i);
                    L = fmaf(fi, __shfl_sync(0xffffffffu, __uint_as_float(ml.y), i), L);
                    o0 = fmaf(fi, __uint_as_float(ov[i].x), o0);
                    o1 = fmaf(fi, __uint_as_float(ov[i].y), o1);
                }
                const float inv = __fdividef(1.0f, L);
                *reinterpret_cast<uint32_t*>(smem + OFF_OB + (b * OB_PITCH + 2 * dp) * 2) = pack_bf2(o0 * inv, o1 * inv);
            }
            cons_bar();
            if (tid < N_OWN) st_rlx(g_sig + tid * 128 + h, tag);
            if (tid == 0) TL(8);
            float acc[5][4];
#pragma unroll
            for (int i = 0; i < 5; i++) { acc[i][0] = acc[i][1] = acc[i][2] = acc[i][3] = 0.f; }
            const uint32_t ab = sb + OFF_OB + (g * OB_PITCH + 2 * c) * 2;
#pragma unroll
            for (int ks = 0; ks < 8; ks++) {
                if (ks < WO_PRE) rows_mma(acc, wf[ks], ab + ks * 32, lane);
                else {
                    uint32_t a[5][4];
                    mbar_wait(bars + (BAR_W + ks) * 8, 0);
                    rows_load(a, (ks < 3 ? reg0 : ks < 6 ? reg1 : reg2) + (ks % 3) * 16 * W_PITCH, warp, lane);
                    rows_mma(acc, a, ab + ks * 32, lane);
                }
            }
            rows_store<NH>(acc, g_att, h, warp, lane);
            if (tid == 0) TL(9);
        }
        float* ored = reinterpret_cast<float*>(smem + OFF_ORED);
        owner_gather<2>(g_att + own * NH * 64, ored, warp, tid, g_sig + own * 128, tag, true);
        cons_bar();
        float h0 = 0.f, h1 = 0.f;
        if (tid < 32 * H_REP) {
            const float2 a = owner_sum(ored, opr, ob);
            const uint32_t ar = pack_bf2(a.x, a.y);
            const uint32_t hr = pack_bf2(bf_lo(xw) + bf_lo(ar), bf_hi(xw) + bf_hi(ar));
            st_rlx(g_h + ((tid >> 5) * NB + ob) * (DM / 2) + own * 8 + opr, nzb(hr));
            h0 = bf_lo(hr); h1 = bf_hi(hr);
        }
        if (tid == 0) TL(10);
        cons_bar();
        if (is_wo) {
            const int b = tid >> 6, dp = tid & 63;
            float* gp = g_part + (size_t)((b * NH + own) * NSLOT) * PART_STRIDE;
            static_for<NSLOT>([&](auto I) { constexpr int i = decltype(I)::value; st_rlx2<i * PART_STRIDE * 4>(gp + 2 * dp, 0, 0); });
            if (dp < NSLOT) st_rlx2(gp + dp * PART_STRIDE + 128, 0, 0);
            st_rlx(g_q + (b * NH + own) * 64 + dp, 0);
        }
        owner_gather<6>(g_y + own * N_FFN * 64, ored + 512, warp, tid, g_sig + own * 128 + 32, tag, false);
        cons_bar();
        if (tid == 0) TL(24);
        if (tid < 32) {
            const float2 y = owner_sum(ored + 512, opr, ob);
            const uint32_t yr = pack_bf2(y.x, y.y);
            *reinterpret_cast<uint32_t*>(out + ob * DM + own * 16 + 2 * opr) = pack_bf2(h0 + bf_lo(yr), h1 + bf_hi(yr));
            if (tid == 0) TL(13);
        }
    } else {
        if (warp < 4) wait_ready(lane, tag);
        uint32_t wf[9][3][4];
        {
            mbar_wait(bars + (BAR_W + warp) * 8, 0);
            const uint32_t arow = ((warp >> 2) ? reg1 : reg0) + ((warp & 3) * GU_BOXROWS + (lane & 7) + 8 * (lane >> 4)) * GU_PITCH + ((lane >> 3) & 1) * 16;
#pragma unroll
            for (int ks = 0; ks < 9; ks++)
#pragma unroll
                for (int i = 0; i < 3; i++) ldsm4t(wf[ks][i], arow + ks * 16 * GU_PITCH + i * 32);
        }
        if (warp < 4) {
            const uint32_t* hp = g_h + ((cta & (H_REP - 1)) * NB + warp) * (DM / 2);
            uint32_t spins = 0;
            {
                const uint32_t* pp = hp + (lane % H_ARM) * (DM / 2 / H_ARM) + (cta >> 2);
                while (!__any_sync(0xffffffffu, lane < H_ARM && ld_rlx(pp))) spin_guard(spins);
            }
            if (tid == 0) TL(7);
            uint32_t hw[9];
#pragma unroll
            for (int i = 0; i < 9; i++) hw[i] = 0;
            while (true) {
                static_for<9>([&](auto I) { constexpr int i = decltype(I)::value; if (!hw[i]) hw[i] = ld_rlx<i * 128>(hp + lane); });
                bool ok = true;
#pragma unroll
                for (int i = 0; i < 9; i++) ok = ok && hw[i];
                if (ok) break;
                spin_guard(spins);
            }
            __syncwarp();
            if (tid == 0) TL(8);
            warp_layernorm(hw);
            uint32_t* hn = reinterpret_cast<uint32_t*>(smem + OFF_HN) + warp * (HN_PITCH / 2);
#pragma unroll
            for (int i = 0; i < 9; i++) hn[lane + 32 * i] = hw[i];
        }
        cons_bar();
        if (tid == 0) TL(9);
        {
            const uint32_t hb = sb + OFF_HN + (g * HN_PITCH + (warp & 3) * GU_BOXROWS + 2 * c) * 2;
            uint32_t bf[9][2];
#pragma unroll
            for (int ks = 0; ks < 9; ks++) {
                bf[ks][0] = bf[ks][1] = 0;
                if (lane < 16) { bf[ks][0] = lds32(hb + ks * 32); bf[ks][1] = lds32(hb + ks * 32 + 16); }
            }
            float acc[2][3][4];
#pragma unroll
            for (int i = 0; i < 6; i++) { acc[i / 3][i % 3][0] = acc[i / 3][i % 3][1] = acc[i / 3][i % 3][2] = acc[i / 3][i % 3][3] = 0.f; }
#pragma unroll
            for (int ks = 0; ks < 9; ks++)
#pragma unroll
                for (int i = 0; i < 3; i++) mma16816(acc[ks & 1][i], wf[ks][i], bf[ks][0], bf[ks][1]);
            float* gu = reinterpret_cast<float*>(smem + OFF_GU) + warp * FC * 4;
            if (c < 2) {
#pragma unroll
                for (int i = 0; i < 3; i++) {
                    *reinterpret_cast<float2*>(gu + (i * 16 + g) * 4 + 2 * c) = make_float2(acc[0][i][0] + acc[1][i][0], acc[0][i][1] + acc[1][i][1]);
                    *reinterpret_cast<float2*>(gu + (i * 16 + g + 8) * 4 + 2 * c) = make_float2(acc[0][i][2] + acc[1][i][2], acc[0][i][3] + acc[1][i][3]);
                }
            }
        }
        cons_bar();
        if (tid >= 192 && tid < 192 + N_OWN) st_rlx(g_sig + (tid - 192) * 128 + 32 + cta, tag);
        if (tid == 192) TL(25);
        if (tid == 0) TL(10);
        if (tid < FC * 4) {
            const float* gu = reinterpret_cast<const float*>(smem + OFF_GU);
            float gv[4], uv[4];
#pragma unroll
            for (int k = 0; k < 4; k++) { gv[k] = gu[k * FC * 4 + tid]; uv[k] = gu[(4 + k) * FC * 4 + tid]; }
            const uint32_t r = pack_bf2((gv[0] + gv[1]) + (gv[2] + gv[3]), (uv[0] + uv[1]) + (uv[2] + uv[3]));
            const float gs = bf_lo(r), us = bf_hi(r);
            const float z = 0.7978845608028654f * fmaf(0.044715f * gs * gs, gs, gs);
            const float ge = bf16r(__fdividef(gs, 1.0f + ex2(z * (-2.0f * LOG2E))));
            reinterpret_cast<__nv_bfloat16*>(smem + OFF_ACT)[(tid & 3) * ACT_PITCH + (tid >> 2)] = __float2bfloat16_rn(ge * us);
        }
        uint32_t wdf[3][5][4];
#pragma unroll
        for (int ks = 0; ks < 3; ks++) {
            mbar_wait(bars + (BAR_W + 8 + ks) * 8, 0);
            rows_load(wdf[ks], reg2 + ks * 16 * W_PITCH, warp, lane);
        }
        cons_bar();
        float acc[5][4];
#pragma unroll
        for (int i = 0; i < 5; i++) { acc[i][0] = acc[i][1] = acc[i][2] = acc[i][3] = 0.f; }
        if (tid == 0) TL(11);
        const uint32_t ab = sb + OFF_ACT + (g * ACT_PITCH + 2 * c) * 2;
#pragma unroll
        for (int ks = 0; ks < 3; ks++) rows_mma(acc, wdf[ks], ab + ks * 32, lane);
        rows_store<N_FFN>(acc, g_y, cta, warp, lane);
        if (tid == 0) TL(12);
        if (tid == 96) TL(26);
        if (tid == 224) TL(27);
    }
    if (tid == 0) TLA(2);
}

#define CFG_PROMO CU_TENSOR_MAP_L2_PROMOTION_L2_256B
typedef CUresult (*EncodeFn)(CUtensorMap*, CUtensorMapDataType, cuuint32_t, void*, const cuuint64_t*, const cuuint64_t*,
                             const cuuint32_t*, const cuuint32_t*, CUtensorMapInterleave, CUtensorMapSwizzle,
                             CUtensorMapL2promotion, CUtensorMapFloatOOBfill);

bool make_map(EncodeFn enc, CUtensorMap* m, const void* ptr) {
    const cuuint64_t dims[2] = {(cuuint64_t)DF, (cuuint64_t)DM};
    const cuuint64_t strides[1] = {(cuuint64_t)DF * 2};
    const cuuint32_t box[2] = {GU_PITCH / 2, GU_BOXROWS};
    const cuuint32_t estr[2] = {1, 1};
    return enc(m, CU_TENSOR_MAP_DATA_TYPE_BFLOAT16, 2, const_cast<void*>(ptr), dims, strides, box, estr,
               CU_TENSOR_MAP_INTERLEAVE_NONE, CU_TENSOR_MAP_SWIZZLE_NONE, CFG_PROMO,
               CU_TENSOR_MAP_FLOAT_OOB_FILL_NONE) == CUDA_SUCCESS;
}

}

extern "C" void kernel_launch(void* const* d_in, const int* in_sizes, int n_in, void* d_out, int out_size) {
    (void)in_sizes; (void)n_in; (void)out_size;
    const __nv_bfloat16* x = (const __nv_bfloat16*)d_in[0];
    const __nv_bfloat16* kc = (const __nv_bfloat16*)d_in[1];
    const __nv_bfloat16* vc = (const __nv_bfloat16*)d_in[2];
    const __nv_bfloat16* wq = (const __nv_bfloat16*)d_in[3];
    const __nv_bfloat16* wo = (const __nv_bfloat16*)d_in[4];
    const void* wg = d_in[6];
    const void* wu = d_in[7];
    const __nv_bfloat16* wd = (const __nv_bfloat16*)d_in[8];

    static EncodeFn enc = nullptr;
    static int sms = 0;
    if (!enc) {
        void* fn = nullptr;
        cudaDriverEntryPointQueryResult qr;
        cudaGetDriverEntryPoint("cuTensorMapEncodeTiled", &fn, cudaEnableDefault, &qr);
        enc = (EncodeFn)fn;
        int dev = 0;
        cudaGetDevice(&dev);
        cudaDeviceGetAttribute(&sms, cudaDevAttrMultiProcessorCount, dev);
        cudaFuncSetAttribute(decode_layer_kernel, cudaFuncAttributeMaxDynamicSharedMemorySize, SMEM_BYTES);
    }
    if (!enc || sms < GRID) return;
    CUtensorMap mg, mu;
    if (!make_map(enc, &mg, wg) || !make_map(enc, &mu, wu)) return;
    decode_layer_kernel<<<GRID, NTHREADS, SMEM_BYTES, cudaStreamPerThread>>>(x, kc, vc, wq, wo, wd, (__nv_bfloat16*)d_out, mg, mu);
}
```

```cpp
#include <cuda_runtime.h>
#include <cuda_bf16.h>
#include <cuda.h>
#include <stdint.h>
#include <type_traits>

namespace {

constexpr int NB = 4, DM = 576, NH = 32, SK = 8192, DH = 128, DF = 4608;
constexpr int NBH = NB * NH;
constexpr int TILE = 128;
constexpr int TILE_BYTES = TILE * DH * 2;
constexpr int NTILES = SK / TILE;
constexpr int NPAIR = 3;

constexpr int N_FFN = 96;
constexpr int N_OUT = 72;
constexpr int N_OWN = 36;
constexpr int GRID = N_FFN + N_OWN;
constexpr int FC = DF / N_FFN;

constexpr int NLAST = 16;
constexpr int NFULL = (NBH - NH) * NTILES;
constexpr int MLAST = NTILES - NLAST;
constexpr int NMAIN = NFULL + NH * MLAST;
constexpr int NPOOL = NBH * NTILES;
constexpr int RING = 16;
constexpr int T_WO = NPOOL - 380;
constexpr int T_END = NPOOL - 32;
constexpr int T_PEEK = T_END - 192;
constexpr int FOLD_CH = 8;
static_assert(NH % (2 * RING) == 0 && MLAST % (2 * FOLD_CH) == 0 && NTILES % (2 * FOLD_CH) == 0 && NLAST == 16, "schedule");
constexpr int NF = 2, NF_END = 4;
constexpr int ISSUE_GAP = 500;
constexpr int W_GAP = 1000;
constexpr int HOLD = 60;

constexpr int PART_STRIDE = 136;
constexpr int H_REP = 4;
constexpr int H_ARM = 3;
constexpr int GU_PITCH = FC * 2;
constexpr int GU_BOXROWS = 144;
constexpr int GU_BOX_BYTES = GU_BOXROWS * GU_PITCH;
constexpr int W_PIECE = 16 * DM * 2;
constexpr int NCONS = 256;
constexpr int NTHREADS = NCONS + 128;

constexpr int OFF_Q = 2 * NPAIR * TILE_BYTES;
constexpr int OFF_DESC = OFF_Q + 8 * 256;
constexpr int OFF_BAR = OFF_DESC + 8 * 8;
constexpr int OFF_TAG = OFF_BAR + 320;
constexpr int OFF_RED = OFF_TAG + 16;
constexpr int OFF_FOLD = OFF_RED + 2 * 8 * PART_STRIDE * 4;
constexpr int OFF_U = OFF_FOLD + 512;
constexpr int OFF_XN = OFF_U;
constexpr int OFF_QRED = OFF_XN + DM * 16;
constexpr int HN_PITCH = 584, ACT_PITCH = 56, OB_PITCH = 136;
constexpr int OFF_HN = OFF_U;
constexpr int OFF_GU = OFF_HN + 4 * HN_PITCH * 2;
constexpr int OFF_STAT = OFF_GU + 8 * FC * 6 * 4;
constexpr int OFF_ACT = OFF_STAT + 48;
constexpr int OFF_OB = OFF_ACT + 4 * ACT_PITCH * 2;
constexpr int SMEM_BYTES = OFF_OB + 4 * OB_PITCH * 2;
static_assert(SMEM_BYTES >= OFF_QRED + 8 * 128 * 4 && SMEM_BYTES <= 232448 && OFF_RED % 16 == 0, "smem");

constexpr int BAR_FULL = 0, BAR_EMPTY = 6, BAR_DESC = 12, BAR_W = 20, BAR_LATE = 31, BAR_RFULL = 32, BAR_RFREE = 34,
              BAR_MFULL = 36, BAR_CLEAN = 38;

constexpr float LOG2E = 1.4426950408889634f;
constexpr float SM_SCALE = 0.08838834764831845f;
constexpr float LN_EPS = 1e-5f;

struct alignas(128) Ctr { unsigned v; unsigned pad[31]; };
__device__ Ctr g_pool, g_done, g_epoch;
__device__ __align__(128) uint32_t g_q[NBH * DH / 2];
__device__ __align__(128) float g_part[(NBH + NH * NLAST) * PART_STRIDE];
__device__ __align__(128) float g_ring[RING * NTILES * PART_STRIDE];
__device__ Ctr g_free[RING];
__device__ __align__(128) float g_att[N_OWN * NH * 64];
__device__ __align__(128) uint32_t g_h[H_REP * NB * DM / 2];
__device__ __align__(128) float g_y[N_OUT * N_FFN * 32];
__device__ __align__(128) uint32_t g_ready[128];

__device__ __forceinline__ void die() { asm volatile("st.volatile.global.u32 [%0], %1;" ::"l"(0ull), "r"(0u) : "memory"); }
__device__ __forceinline__ uint32_t smem_u32(const void* p) { return (uint32_t)__cvta_generic_to_shared(p); }
__device__ __forceinline__ void mbar_init(uint32_t bar, uint32_t cnt) {
    asm volatile("mbarrier.init.shared::cta.b64 [%0], %1;" ::"r"(bar), "r"(cnt) : "memory");
}
__device__ __forceinline__ void mbar_expect_tx(uint32_t bar, uint32_t bytes) {
    asm volatile("mbarrier.arrive.expect_tx.shared::cta.b64 _, [%0], %1;" ::"r"(bar), "r"(bytes) : "memory");
}
__device__ __forceinline__ void mbar_arrive(uint32_t bar) {
    asm volatile("mbarrier.arrive.shared::cta.b64 _, [%0];" ::"r"(bar) : "memory");
}
__device__ __forceinline__ void mbar_arrive_after(uint32_t bar, uint32_t dep) {
    asm volatile("{\n.reg .u32 t;\nor.b32 t, %1, 1;\nmin.u32 t, t, 1;\nmbarrier.arrive.shared::cta.b64 _, [%0], t;\n}"
                 ::"r"(bar), "r"(dep) : "memory");
}
__device__ __forceinline__ bool mbar_try(uint32_t bar, uint32_t parity) {
    uint32_t ok;
    asm volatile("{\n.reg .pred p;\nmbarrier.try_wait.parity.shared::cta.b64 p, [%1], %2;\nselp.u32 %0, 1, 0, p;\n}"
                 : "=r"(ok) : "r"(bar), "r"(parity) : "memory");
    return ok != 0;
}
__device__ __forceinline__ bool mbar_test(uint32_t bar, uint32_t parity) {
    uint32_t ok;
    asm volatile("{\n.reg .pred p;\nmbarrier.test_wait.parity.shared::cta.b64 p, [%1], %2;\nselp.u32 %0, 1, 0, p;\n}"
                 : "=r"(ok) : "r"(bar), "r"(parity) : "memory");
    return ok != 0;
}
__device__ __forceinline__ void mbar_wait(uint32_t bar, uint32_t parity) {
    uint32_t spins = 0;
    while (!mbar_try(bar, parity)) {
        if (++spins > (1u << 20)) die();
    }
}
__device__ __forceinline__ void bulk_g2s(uint32_t dst, const void* src, uint32_t bytes, uint32_t bar) {
    asm volatile("cp.async.bulk.shared::cluster.global.mbarrier::complete_tx::bytes [%0], [%1], %2, [%3];"
                 ::"r"(dst), "l"(src), "r"(bytes), "r"(bar) : "memory");
}
__device__ __forceinline__ void bulk_g2s_hint(uint32_t dst, const void* src, uint32_t bytes, uint32_t bar, uint64_t pol) {
    asm volatile("cp.async.bulk.shared::cluster.global.mbarrier::complete_tx::bytes.L2::cache_hint [%0], [%1], %2, [%3], %4;"
                 ::"r"(dst), "l"(src), "r"(bytes), "r"(bar), "l"(pol) : "memory");
}
__device__ __forceinline__ void tma_2d(uint32_t dst, const CUtensorMap* map, int c0, int c1, uint32_t bar, uint64_t pol) {
    asm volatile("cp.async.bulk.tensor.2d.shared::cluster.global.mbarrier::complete_tx::bytes.L2::cache_hint [%0], [%1, {%3, %4}], [%2], %5;"
                 ::"r"(dst), "l"(map), "r"(bar), "r"(c0), "r"(c1), "l"(pol) : "memory");
}
__device__ __forceinline__ void tma_3d(uint32_t dst, const CUtensorMap* map, int c2, uint32_t bar, uint64_t pol) {
    asm volatile("cp.async.bulk.tensor.3d.shared::cluster.global.mbarrier::complete_tx::bytes.L2::cache_hint [%0], [%1, {%3, %3, %4}], [%2], %5;"
                 ::"r"(dst), "l"(map), "r"(bar), "r"(0), "r"(c2), "l"(pol) : "memory");
}
__device__ __forceinline__ unsigned atom_add_relaxed(unsigned* p, unsigned v) {
    unsigned o;
    asm volatile("atom.relaxed.gpu.global.add.u32 %0, [%1], %2;" : "=r"(o) : "l"(p), "r"(v) : "memory");
    return o;
}
template <int OFF = 0>
__device__ __forceinline__ uint32_t ld_rlx(const void* p) {
    uint32_t v;
    asm volatile("ld.relaxed.gpu.global.u32 %0, [%1+%2];" : "=r"(v) : "l"(p), "n"(OFF) : "memory");
    return v;
}
__device__ __forceinline__ uint32_t ld_acq(const void* p) {
    uint32_t v;
    asm volatile("ld.acquire.gpu.global.u32 %0, [%1];" : "=r"(v) : "l"(p) : "memory");
    return v;
}
template <int OFF = 0>
__device__ __forceinline__ uint2 ld_rlx2(const void* p) {
    uint2 v;
    asm volatile("ld.relaxed.gpu.global.v2.u32 {%0,%1}, [%2+%3];" : "=r"(v.x), "=r"(v.y) : "l"(p), "n"(OFF) : "memory");
    return v;
}
template <int OFF = 0>
__device__ __forceinline__ uint4 ld_rlx4(const void* p) {
    uint4 v;
    asm volatile("ld.relaxed.gpu.global.v4.u32 {%0,%1,%2,%3}, [%4+%5];" : "=r"(v.x), "=r"(v.y), "=r"(v.z), "=r"(v.w) : "l"(p), "n"(OFF) : "memory");
    return v;
}
__device__ __forceinline__ void st_rlx(void* p, uint32_t v) {
    asm volatile("st.relaxed.gpu.global.u32 [%0], %1;" ::"l"(p), "r"(v) : "memory");
}
template <int OFF = 0>
__device__ __forceinline__ void st_rlx2(void* p, uint32_t a, uint32_t b) {
    asm volatile("st.relaxed.gpu.global.v2.u32 [%0+%3], {%1,%2};" ::"l"(p), "r"(a), "r"(b), "n"(OFF) : "memory");
}
__device__ __forceinline__ void st_rlx4(void* p, uint32_t a, uint32_t b, uint32_t c, uint32_t d) {
    asm volatile("st.relaxed.gpu.global.v4.u32 [%0], {%1,%2,%3,%4};" ::"l"(p), "r"(a), "r"(b), "r"(c), "r"(d) : "memory");
}
__device__ __forceinline__ void put(void* p, uint32_t a) {
    asm volatile("red.relaxed.gpu.global.or.b32 [%0], %1;" ::"l"(p), "r"(a) : "memory");
}
template <int OFF = 0>
__device__ __forceinline__ void put2(void* p, uint32_t a, uint32_t b) {
    asm volatile("{\n.reg .b64 t;\nmov.b64 t, {%1,%2};\nred.relaxed.gpu.global.or.b64 [%0+%3], t;\n}"
                 ::"l"(p), "r"(a), "r"(b), "n"(OFF) : "memory");
}
template <int N, class F>
__device__ __forceinline__ void static_for(F&& f) {
    if constexpr (N > 0) { static_for<N - 1>(f); f(std::integral_constant<int, N - 1>{}); }
}
__device__ __forceinline__ uint32_t nzb(uint32_t u) { uint32_t r; asm("max.u32 %0, %1, 1;" : "=r"(r) : "r"(u)); return r; }
__device__ __forceinline__ uint32_t nzf(float v) { return nzb(__float_as_uint(v)); }
__device__ __forceinline__ uint32_t mark(float v, uint32_t par) { return (__float_as_uint(v) & ~1u) | par; }
__device__ __forceinline__ float unmark(uint32_t u) { return __uint_as_float(u & ~1u); }
template <class T>
__device__ __forceinline__ T* pin(T* p, uint32_t z) {
    T* q;
    asm volatile("add.u64 %0, %1, %2;" : "=l"(q) : "l"(p), "l"((uint64_t)z));
    return q;
}
__device__ __forceinline__ bool ok4(const uint4& v) { return v.x && v.y && v.z && v.w; }
__device__ __forceinline__ void spin_guard(uint32_t& spins) { if (++spins > (1u << 23)) die(); }
__device__ __forceinline__ uint32_t pack_bf2(float lo, float hi) {
    const __nv_bfloat162 v = __floats2bfloat162_rn(lo, hi);
    return *reinterpret_cast<const uint32_t*>(&v);
}
__device__ __forceinline__ void cons_bar() { asm volatile("bar.sync 1, 256;" ::: "memory"); }
__device__ __forceinline__ void ldsm4(uint32_t (&r)[4], uint32_t addr) {
    asm volatile("ldmatrix.sync.aligned.m8n8.x4.shared.b16 {%0,%1,%2,%3}, [%4];"
                 : "=r"(r[0]), "=r"(r[1]), "=r"(r[2]), "=r"(r[3]) : "r"(addr) : "memory");
}
__device__ __forceinline__ void ldsm4t(uint32_t (&r)[4], uint32_t addr) {
    asm volatile("ldmatrix.sync.aligned.m8n8.x4.trans.shared.b16 {%0,%1,%2,%3}, [%4];"
                 : "=r"(r[0]), "=r"(r[1]), "=r"(r[2]), "=r"(r[3]) : "r"(addr) : "memory");
}
__device__ __forceinline__ void mma16816(float (&c)[4], const uint32_t (&a)[4], uint32_t b0, uint32_t b1) {
    asm volatile("mma.sync.aligned.m16n8k16.row.col.f32.bf16.bf16.f32 {%0,%1,%2,%3}, {%4,%5,%6,%7}, {%8,%9}, {%0,%1,%2,%3};"
                 : "+f"(c[0]), "+f"(c[1]), "+f"(c[2]), "+f"(c[3])
                 : "r"(a[0]), "r"(a[1]), "r"(a[2]), "r"(a[3]), "r"(b0), "r"(b1));
}
__device__ __forceinline__ float bf16r(float x) { return __uint_as_float(pack_bf2(0.f, x) & 0xffff0000u); }
__device__ __forceinline__ float bf_lo(uint32_t u) { return __uint_as_float(u << 16); }
__device__ __forceinline__ float bf_hi(uint32_t u) { return __uint_as_float(u & 0xffff0000u); }
__device__ __forceinline__ float ex2(float x) { float y; asm("ex2.approx.ftz.f32 %0, %1;" : "=f"(y) : "f"(x)); return y; }
__device__ __forceinline__ float warp_sum(float v) {
#pragma unroll
    for (int o = 16; o > 0; o >>= 1) v += __shfl_xor_sync(0xffffffffu, v, o);
    return v;
}
__device__ __forceinline__ float warp_max(float v) {
#pragma unroll
    for (int o = 16; o > 0; o >>= 1) v = fmaxf(v, __shfl_xor_sync(0xffffffffu, v, o));
    return v;
}
__device__ __forceinline__ uint32_t lds32(uint32_t a) { uint32_t v; asm volatile("ld.shared.u32 %0, [%1];" : "=r"(v) : "r"(a) : "memory"); return v; }

__device__ __forceinline__ float2 ln_finish(float k, float s, float q) {
    const float dm = s * (1.0f / DM);
    const uint32_t mv = pack_bf2(k + dm, fmaxf(fmaf(-dm, dm, q * (1.0f / DM)), 0.f));
    float sd, rs;
    asm("sqrt.approx.ftz.f32 %0, %1;" : "=f"(sd) : "f"(bf16r(bf_hi(mv) + LN_EPS)));
    asm("rcp.approx.ftz.f32 %0, %1;" : "=f"(rs) : "f"(bf16r(sd)));
    return make_float2(bf_lo(mv), rs);
}
__device__ __forceinline__ void warp_layernorm(uint32_t (&w)[9]) {
    const float k = bf_lo(__shfl_sync(0xffffffffu, w[0], 0));
    float s0 = 0.f, s1 = 0.f, q0 = 0.f, q1 = 0.f;
#pragma unroll
    for (int i = 0; i < 9; i++) {
        const float a = bf_lo(w[i]) - k, b = bf_hi(w[i]) - k;
        s0 += a; s1 += b; q0 = fmaf(a, a, q0); q1 = fmaf(b, b, q1);
    }
    float s = s0 + s1, q = q0 + q1;
#pragma unroll
    for (int o = 16; o > 0; o >>= 1) { s += __shfl_xor_sync(0xffffffffu, s, o); q += __shfl_xor_sync(0xffffffffu, q, o); }
    const float2 st = ln_finish(k, s, q);
#pragma unroll
    for (int i = 0; i < 9; i++) {
        const uint32_t d = pack_bf2(bf_lo(w[i]) - st.x, bf_hi(w[i]) - st.x);
        w[i] = pack_bf2(bf_lo(d) * st.y, bf_hi(d) * st.y);
    }
}

__device__ __forceinline__ void pool_item(unsigned idx, int& bh, int& tile, int& slot) {
    if (idx < NFULL) {
        bh = idx / NTILES; tile = idx % NTILES; slot = -1 - tile;
    } else if (idx < NMAIN) {
        const int e = idx - NFULL;
        bh = NBH - NH + e / MLAST; tile = e % MLAST; slot = -1 - tile;
    } else {
        const int e = idx - NMAIN;
        bh = NBH - NH + e / NLAST; tile = MLAST + e % NLAST; slot = NBH + e;
    }
}

__device__ __forceinline__ void rows_load(uint32_t (&a)[5][4], uint32_t wrows, int warp, int lane) {
    const int cc = 2 * warp + ((lane >> 3) & 1), line = 9 * ((lane & 7) + 8 * (lane >> 4)) + (cc >> 3);
    const uint32_t arow = wrows + line * 128;
#pragma unroll
    for (int i = 0; i < 4; i++) ldsm4t(a[i], arow + i * 256 + (((cc ^ (line + 2 * i)) & 7) << 4));
    if (warp < 4) ldsm4t(a[4], arow + 4 * 256 + (((cc ^ line) & 7) << 4));
}
template <int NK>
__device__ __forceinline__ void rows_mma(float (&acc)[5][4], const uint32_t (&a)[NK][5][4], uint32_t act, int warp, int lane) {
    uint32_t b[NK][2];
#pragma unroll
    for (int ks = 0; ks < NK; ks++) { b[ks][0] = lds32(act + ks * 32); b[ks][1] = lds32(act + ks * 32 + 16); }
#pragma unroll
    for (int ks = 0; ks < NK; ks++) {
#pragma unroll
        for (int i = 0; i < 4; i++) mma16816(acc[i], a[ks][i], b[ks][0], b[ks][1]);
        if (warp < 4) mma16816(acc[4], a[ks][4], b[ks][0], b[ks][1]);
    }
}
template <int STEP>
__device__ __forceinline__ void rows_store(const float (&acc)[5][4], float* d, int warp, int lane) {
    const bool hi = lane & 2;
    static_for<5>([&](auto I) {
        constexpr int i = decltype(I)::value;
        if (i < 4 || warp < 4) put2<i * STEP>(d, nzf(hi ? acc[i][2] : acc[i][0]), nzf(hi ? acc[i][3] : acc[i][1]));
    });
}
template <int R>
__device__ __forceinline__ float4 gather_sum(const float* p) {
    uint4 v[R];
    uint32_t pending = (1u << R) - 1, spins = 0;
    while (true) {
        static_for<R>([&](auto I) { constexpr int r = decltype(I)::value; if (pending >> r & 1) v[r] = ld_rlx4<r * NCONS * 16>(p); });
#pragma unroll
        for (int r = 0; r < R; r++)
            if (ok4(v[r])) pending &= ~(1u << r);
        if (!__any_sync(0xffffffffu, pending)) break;
        spin_guard(spins);
    }
    float4 a = make_float4(__uint_as_float(v[0].x), __uint_as_float(v[0].y), __uint_as_float(v[0].z), __uint_as_float(v[0].w));
#pragma unroll
    for (int r = 1; r < R; r++) {
        a.x += __uint_as_float(v[r].x); a.y += __uint_as_float(v[r].y); a.z += __uint_as_float(v[r].z); a.w += __uint_as_float(v[r].w);
    }
    return a;
}
template <int STRIDE>
__device__ __forceinline__ float2 warps_sum(const float* p) {
    float2 v[8];
#pragma unroll
    for (int w8 = 0; w8 < 8; w8++) v[w8] = *reinterpret_cast<const float2*>(p + w8 * STRIDE);
    return make_float2(((v[0].x + v[1].x) + (v[2].x + v[3].x)) + ((v[4].x + v[5].x) + (v[6].x + v[7].x)),
                       ((v[0].y + v[1].y) + (v[2].y + v[3].y)) + ((v[4].y + v[5].y) + (v[6].y + v[7].y)));
}
template <int N>
__device__ __forceinline__ void wait_ready(int lane, uint32_t tag) {
    uint32_t spins = 0;
    while (true) {
        bool ok = true;
#pragma unroll
        for (int i = 0; i < (N + 31) / 32; i++) ok = (lane + 32 * i >= N || ld_acq(g_ready + lane + 32 * i) == tag) && ok;
        if (__all_sync(0xffffffffu, ok)) break;
        spin_guard(spins);
    }
}

__global__ void __launch_bounds__(NTHREADS, 1)
decode_layer_kernel(const __nv_bfloat16* __restrict__ x, const __nv_bfloat16* __restrict__ kc,
                    const __nv_bfloat16* __restrict__ vc, const __nv_bfloat16* __restrict__ wq,
                    __nv_bfloat16* __restrict__ out,
                    const __grid_constant__ CUtensorMap map_g, const __grid_constant__ CUtensorMap map_u,
                    const __grid_constant__ CUtensorMap map_d, const __grid_constant__ CUtensorMap map_o) {
    extern __shared__ __align__(1024) unsigned char smem[];
    const uint32_t sb = smem_u32(smem);
    const int tid = threadIdx.x, warp = __shfl_sync(0xffffffffu, tid >> 5, 0), lane = tid & 31;
    const int cta = blockIdx.x;
    const bool is_ffn = cta < N_FFN;
    const bool is_wo = cta >= N_FFN && cta < NBH;
    const uint32_t bars = sb + OFF_BAR;
    volatile int2* desc = reinterpret_cast<volatile int2*>(smem + OFF_DESC);

    if (warp >= 8) {
        uint32_t tag = 0;
        uint64_t pol = 0;
        int bh, tile, slot;
        pool_item(cta, bh, tile, slot);
        if (tid == NCONS) {
            mbar_init(bars + BAR_FULL * 8, 1);
            mbar_init(bars + (BAR_FULL + 1) * 8, 1);
            asm volatile("fence.mbarrier_init.release.cluster;" ::: "memory");
            asm volatile("fence.proxy.async.shared::cta;" ::: "memory");
            asm volatile("createpolicy.fractional.L2::evict_first.b64 %0, 1.0;" : "=l"(pol));
            const size_t off = (size_t)(bh * NTILES + tile) * TILE_BYTES;
#pragma unroll
            for (int i = 0; i < 2; i++) {
                mbar_expect_tx(bars + (BAR_FULL + i) * 8, TILE_BYTES);
                bulk_g2s_hint(sb + i * TILE_BYTES, (const char*)(i ? vc : kc) + off, TILE_BYTES, bars + (BAR_FULL + i) * 8, pol);
            }
            tag = ld_rlx(&g_epoch.v) + 1;
#pragma unroll
            for (int i = 0; i < 6; i++) { if (i >= 2) mbar_init(bars + (BAR_FULL + i) * 8, 1); mbar_init(bars + (BAR_EMPTY + i) * 8, 8); }
#pragma unroll
            for (int i = 0; i < 8; i++) mbar_init(bars + (BAR_DESC + i) * 8, 1);
#pragma unroll
            for (int i = 0; i < 12; i++) mbar_init(bars + (BAR_W + i) * 8, 1);
#pragma unroll
            for (int i = 0; i < 2; i++) {
                mbar_init(bars + (BAR_RFULL + i) * 8, 8); mbar_init(bars + (BAR_MFULL + i) * 8, 8); mbar_init(bars + (BAR_RFREE + i) * 8, 1);
            }
            mbar_init(bars + BAR_CLEAN * 8, 1);
            *reinterpret_cast<volatile uint32_t*>(smem + OFF_TAG) = tag;
            *reinterpret_cast<volatile uint32_t*>(smem + OFF_TAG + 4) = 0;
            asm volatile("fence.mbarrier_init.release.cluster;" ::: "memory");
            asm volatile("fence.proxy.async.shared::cta;" ::: "memory");
        }
        __syncwarp();
        asm volatile("setmaxnreg.dec.sync.aligned.u32 72;");
        if (warp == 8) {
            int u = 2;
            asm volatile("bar.arrive 2, 384;" ::: "memory");
            if (lane == 0) {
                if (is_ffn) {
                    asm volatile("prefetch.tensormap [%0];" ::"l"(&map_g) : "memory");
                    asm volatile("prefetch.tensormap [%0];" ::"l"(&map_u) : "memory");
                }
                asm volatile("prefetch.tensormap [%0];" ::"l"(is_ffn ? &map_d : &map_o) : "memory");
                int s = 2; uint32_t ph = 1;
                int sa = 0; uint32_t pa = 0;
                int acked = 0;
                bool late = false;
                auto issue = [&](const void* src, int nf) {
                    while (u - acked >= nf) {
                        mbar_wait(bars + (BAR_FULL + sa) * 8, pa);
                        acked++;
                        if (++sa == 2 * NPAIR) { sa = 0; pa ^= 1; }
                    }
                    if (nf == NF) { const long long t0 = clock64(); while (clock64() - t0 < ISSUE_GAP) {} }
                    mbar_wait(bars + (BAR_EMPTY + s) * 8, ph);
                    mbar_expect_tx(bars + (BAR_FULL + s) * 8, TILE_BYTES);
                    bulk_g2s_hint(sb + s * TILE_BYTES, src, TILE_BYTES, bars + (BAR_FULL + s) * 8, pol);
                    u++;
                    if (++s == 2 * NPAIR) { s = 0; ph ^= 1; }
                };
                auto claim = [&](bool more) {
                    unsigned r = NPOOL;
                    asm volatile("{\n.reg .pred p;\nsetp.ne.u32 p, %2, 0;\n@p atom.relaxed.gpu.global.inc.u32 %0, [%1], 0x7fffffff;\n}"
                                 : "+r"(r) : "l"(&g_pool.v), "r"((uint32_t)more) : "memory");
                    return r;
                };
                unsigned idx = claim(true) + GRID;
                int n = 1;
                for (;; n++) {
                    if (!late && idx >= (unsigned)NMAIN) { mbar_arrive(bars + BAR_LATE * 8); late = true; }
                    if (idx >= (unsigned)NPOOL) break;
                    pool_item(idx, bh, tile, slot);
                    const uint32_t ds = n & 7;
                    desc[ds].x = bh; desc[ds].y = slot;
                    mbar_expect_tx(bars + (BAR_DESC + ds) * 8, 256);
                    bulk_g2s(sb + OFF_Q + ds * 256, g_q + bh * 64, 256, bars + (BAR_DESC + ds) * 8);
                    const size_t off = (size_t)(bh * NTILES + tile) * TILE_BYTES;
                    int nf = idx >= (unsigned)T_END ? NF_END : NF;
                    issue((const char*)kc + off, nf);
                    const unsigned next = claim(!(is_wo && idx >= (unsigned)T_WO));
                    if (idx >= (unsigned)T_PEEK && next + GRID >= (unsigned)T_END) nf = NF_END;
                    issue((const char*)vc + off, nf);
                    idx = next + GRID;
                }
                desc[n & 7].y = 0;
                mbar_arrive(bars + (BAR_DESC + (n & 7)) * 8);
                if (is_ffn) {
                    const long long t0 = clock64(), d = HOLD * max(0, GRID - NH - (int)(idx - NPOOL));
                    while (clock64() - t0 < d) {}
                }
            }
            if (lane == 0 && (is_ffn || is_wo)) {
                const int npieces = is_ffn ? 11 : 8;
                long long tw = 0;
#pragma unroll 1
                for (int i = 0; i < npieces; i++) {
                    const int r = is_ffn ? (i >> 2) : i / 3;
                    const int j = is_ffn ? (i & 3) : i - 3 * r;
                    const int pu = (u >> 1) + r;
                    const int p = pu % NPAIR;
                    const uint32_t dst = sb + 2 * p * TILE_BYTES;
                    const uint32_t wb = bars + (BAR_W + i) * 8;
                    if (is_ffn) {
                        if (i == 0) { const int v = u - 2; mbar_wait(bars + (BAR_FULL + v % (2 * NPAIR)) * 8, (v / (2 * NPAIR)) & 1); tw = clock64(); }
                        if (i >= 4) mbar_wait(bars + (BAR_W + i - 4) * 8, 0);
                        if (i >= 2) { while (clock64() - tw < (i - 1) * W_GAP && !mbar_test(bars + (BAR_W + i - 2) * 8, 0)) {} }
                    }
                    if (j == 0) {
                        const uint32_t pe = ((pu / NPAIR) & 1) ^ 1;
                        mbar_wait(bars + (BAR_EMPTY + 2 * p) * 8, pe);
                        mbar_wait(bars + (BAR_EMPTY + 2 * p + 1) * 8, pe);
                    }
                    if (is_ffn && r < 2) {
                        mbar_expect_tx(wb, GU_BOX_BYTES);
                        tma_2d(dst + j * GU_BOX_BYTES, r == 0 ? &map_g : &map_u, cta * FC, j * GU_BOXROWS, wb, pol);
                    } else {
                        mbar_expect_tx(wb, W_PIECE);
                        tma_3d(dst + j * W_PIECE, is_ffn ? &map_d : &map_o, is_ffn ? cta * FC + j * 16 : (cta - N_FFN) * DH + i * 16, wb, pol);
                    }
                }
            }
            if (lane == 0 && atom_add_relaxed(&g_done.v, 1) == GRID - 1) { g_pool.v = 0; g_done.v = 0; g_epoch.v = tag; }
        } else if (warp == 9) {
            asm volatile("bar.sync 2, 384;" ::: "memory");
            tag = *reinterpret_cast<volatile uint32_t*>(smem + OFF_TAG);
            {
                uint2 qv;
                uint32_t spins = 0;
                do { qv = ld_rlx2(g_q + bh * 64 + 2 * lane); spin_guard(spins); } while (!(qv.x && qv.y));
                *reinterpret_cast<uint2*>(smem + OFF_Q + 8 * lane) = qv;
                __syncwarp();
                if (lane == 0) {
                    desc[0].x = bh; desc[0].y = slot;
                    mbar_arrive(bars + BAR_DESC * 8);
                }
                __syncwarp();
            }
            for (int n = 0;; n++) {
                mbar_wait(bars + (BAR_DESC + (n & 7)) * 8, (n >> 3) & 1);
                const int dbh = desc[n & 7].x, dst = desc[n & 7].y;
                if (dst == 0) break;
                const bool ring = dst < 0;
                float* gp = (ring ? g_ring + ((dbh % RING) * NTILES - 1 - dst) * PART_STRIDE : g_part + dst * PART_STRIDE) + 4 * lane;
                const uint32_t want = tag * NBH + dbh - RING;
                uint32_t seen = want;
                if (ring && dbh >= RING) seen = ld_rlx(&g_free[dbh % RING].v);
                const float* red = reinterpret_cast<const float*>(smem + OFF_RED) + (n & 1) * 8 * PART_STRIDE;
                mbar_wait(bars + (BAR_MFULL + (n & 1)) * 8, (n >> 1) & 1);
                float f[8];
#pragma unroll
                for (int w8 = 0; w8 < 8; w8++) f[w8] = red[w8 * PART_STRIDE + 128];
                const float M = fmaxf(fmaxf(fmaxf(f[0], f[1]), fmaxf(f[2], f[3])), fmaxf(fmaxf(f[4], f[5]), fmaxf(f[6], f[7])));
                float L = 0.f;
#pragma unroll
                for (int w8 = 0; w8 < 8; w8++) { f[w8] = ex2((f[w8] - M) * LOG2E); L = fmaf(f[w8], red[w8 * PART_STRIDE + 129], L); }
                mbar_wait(bars + (BAR_RFULL + (n & 1)) * 8, (n >> 1) & 1);
                float4 o = make_float4(0.f, 0.f, 0.f, 0.f), o2 = o;
#pragma unroll
                for (int w8 = 0; w8 < 8; w8 += 2) {
                    const float4 v = *reinterpret_cast<const float4*>(red + w8 * PART_STRIDE + 4 * lane);
                    const float4 v2 = *reinterpret_cast<const float4*>(red + (w8 + 1) * PART_STRIDE + 4 * lane);
                    o.x = fmaf(f[w8], v.x, o.x); o.y = fmaf(f[w8], v.y, o.y); o.z = fmaf(f[w8], v.z, o.z); o.w = fmaf(f[w8], v.w, o.w);
                    o2.x = fmaf(f[w8 + 1], v2.x, o2.x); o2.y = fmaf(f[w8 + 1], v2.y, o2.y);
                    o2.z = fmaf(f[w8 + 1], v2.z, o2.z); o2.w = fmaf(f[w8 + 1], v2.w, o2.w);
                }
                o.x += o2.x; o.y += o2.y; o.z += o2.z; o.w += o2.w;
                if (ring) {
                    uint32_t spins = 0;
                    while (seen != want) { seen = ld_rlx(&g_free[dbh % RING].v); spin_guard(spins); }
                    const uint32_t par = (dbh / RING + 1) & 1;
                    st_rlx4(gp, mark(o.x, par), mark(o.y, par), mark(o.z, par), mark(o.w, par));
                    if (lane < 2) st_rlx4(gp + 128, mark(M, par), mark(L, par), 0u, 0u);
                } else {
                    st_rlx4(gp, nzf(o.x), nzf(o.y), nzf(o.z), nzf(o.w));
                    if (lane < 2) st_rlx4(gp + 128, nzf(M), nzf(L), 1u, 1u);
                }
                __syncwarp();
                if (lane == 0) mbar_arrive(bars + (BAR_RFREE + (n & 1)) * 8);
            }
        } else {
            asm volatile("bar.sync 2, 384;" ::: "memory");
            tag = *reinterpret_cast<volatile uint32_t*>(smem + OFF_TAG);
            if (cta < NBH) {
                const int fb = (cta + 32) & (NBH - 1);
                const int half = warp - 10;
                const int mm = fb < NBH - NH ? NTILES : MLAST;
                const unsigned taken = fb < NBH - NH ? (fb + 1) * NTILES : NFULL + (fb + 1 - (NBH - NH)) * MLAST;
                uint32_t spins = 0;
                while (!mbar_test(bars + BAR_LATE * 8, 0)) {
                    const int left = (int)(taken - GRID - ld_rlx(&g_pool.v));
                    if (left <= 0) break;
                    __nanosleep(min(left * 8 + 200, 8000));
                    spin_guard(spins);
                }
                const float* row = g_ring + (fb % RING) * NTILES * PART_STRIDE;
                if (fb >= RING) { while (ld_acq(&g_free[fb % RING].v) != tag * NBH + fb - RING) spin_guard(spins); }
                const uint32_t par = (fb / RING + 1) & 1;
                uint2 ma, mb = make_uint2(par, par);
                while (true) {
                    ma = ld_rlx2(row + lane * PART_STRIDE + 128);
                    if (lane + 32 < mm) mb = ld_rlx2(row + (lane + 32) * PART_STRIDE + 128);
                    if (__all_sync(0xffffffffu, !(((ma.x ^ par) | (ma.y ^ par) | (mb.x ^ par) | (mb.y ^ par)) & 1))) break;
                    __nanosleep(200);
                    spin_guard(spins);
                }
                const float m0 = unmark(ma.x), m1 = lane + 32 < mm ? unmark(mb.x) : -INFINITY;
                const float M = warp_max(fmaxf(m0, m1));
                const float f0 = ex2((m0 - M) * LOG2E), f1 = ex2((m1 - M) * LOG2E);
                const float L = warp_sum(f0 * unmark(ma.y) + f1 * unmark(mb.y));
                float4 o = make_float4(0.f, 0.f, 0.f, 0.f);
#pragma unroll 1
                for (int i0 = half * (mm / 2); i0 < (half + 1) * (mm / 2); i0 += FOLD_CH) {
                    const float* pi = row + i0 * PART_STRIDE + 4 * lane;
                    uint4 v[FOLD_CH];
                    while (true) {
                        uint32_t bad = 0;
                        static_for<FOLD_CH>([&](auto I) { constexpr int i = decltype(I)::value; v[i] = ld_rlx4<i * PART_STRIDE * 4>(pi); });
#pragma unroll
                        for (int i = 0; i < FOLD_CH; i++) bad |= (v[i].x ^ par) | (v[i].y ^ par) | (v[i].z ^ par) | (v[i].w ^ par);
                        if (__all_sync(0xffffffffu, !(bad & 1))) break;
                        spin_guard(spins);
                    }
#pragma unroll
                    for (int i = 0; i < FOLD_CH; i++) {
                        const float f = __shfl_sync(0xffffffffu, i0 + i < 32 ? f0 : f1, (i0 + i) & 31);
                        o.x = fmaf(f, unmark(v[i].x), o.x); o.y = fmaf(f, unmark(v[i].y), o.y);
                        o.z = fmaf(f, unmark(v[i].z), o.z); o.w = fmaf(f, unmark(v[i].w), o.w);
                    }
                }
                float4* fold = reinterpret_cast<float4*>(smem + OFF_FOLD);
                if (half) fold[lane] = o;
                asm volatile("bar.sync 4, 64;" ::: "memory");
                if (!half) {
                    const float4 o1 = fold[lane];
                    float* gp = g_part + fb * PART_STRIDE + 4 * lane;
                    st_rlx4(gp, nzf(o.x + o1.x), nzf(o.y + o1.y), nzf(o.z + o1.z), nzf(o.w + o1.w));
                    if (lane < 2) st_rlx4(gp + 128, nzf(M), nzf(L), 1u, 1u);
                    if (lane == 0) st_rlx(&g_free[fb % RING].v, tag * NBH + fb);
                }
            }
            if (warp == 11 && (!is_ffn || cta < N_OUT)) {
                const int own = cta - N_FFN;
                mbar_wait(bars + BAR_LATE * 8, 0);
                if (is_ffn) {
#pragma unroll 4
                    for (int i = lane; i < N_FFN * 8; i += 32) st_rlx4(g_y + cta * N_FFN * 32 + i * 4, 0, 0, 0, 0);
                } else {
#pragma unroll 4
                    for (int i = lane; i < NH * 16; i += 32) st_rlx4(g_att + own * NH * 64 + i * 4, 0, 0, 0, 0);
                    for (int i = lane; i < H_REP * NB * 2; i += 32) st_rlx4(g_h + (i >> 1) * (DM / 2) + own * 8 + (i & 1) * 4, 0, 0, 0, 0);
                }
                __syncwarp();
                if (lane == 0) {
                    asm volatile("fence.acq_rel.gpu;" ::: "memory");
                    st_rlx(g_ready + (is_ffn ? N_OWN + cta : own), tag);
                    mbar_arrive(bars + BAR_CLEAN * 8);
                }
            }
            if (is_ffn) {
                const int b = 2 * (warp - 10) + (lane >> 4);
                const uint32_t* hr = reinterpret_cast<const uint32_t*>(smem + OFF_HN) + b * (HN_PITCH / 2) + (lane & 15);
                asm volatile("bar.sync 5, 320;" ::: "memory");
                const float k = bf_lo(hr[-(lane & 15)]);
                float s0 = 0.f, s1 = 0.f, q0 = 0.f, q1 = 0.f;
#pragma unroll
                for (int i = 0; i < 18; i++) {
                    const uint32_t w = hr[16 * i];
                    const float a0 = bf_lo(w) - k, a1 = bf_hi(w) - k;
                    s0 += a0; s1 += a1; q0 = fmaf(a0, a0, q0); q1 = fmaf(a1, a1, q1);
                }
                float sm = s0 + s1, sq = q0 + q1;
#pragma unroll
                for (int o = 8; o > 0; o >>= 1) { sm += __shfl_xor_sync(0xffffffffu, sm, o); sq += __shfl_xor_sync(0xffffffffu, sq, o); }
                const float2 st = ln_finish(k, sm, sq);
                if ((lane & 15) == 0) reinterpret_cast<float2*>(smem + OFF_STAT)[b] = st;
                __syncwarp();
                asm volatile("bar.arrive 6, 320;" ::: "memory");
            }
        }
        return;
    }

    const int g = lane >> 2, c = lane & 3;
    if (cta < NBH) {
        uint4 w[9];
        const __nv_bfloat16* wp = wq + (size_t)(tid >> 2) * (NH * DH) + cta * 32 + (tid & 3) * 8;
#pragma unroll
        for (int i = 0; i < 9; i++)
            asm volatile("ld.global.nc.L1::no_allocate.v4.u32 {%0,%1,%2,%3}, [%4];"
                         : "=r"(w[i].x), "=r"(w[i].y), "=r"(w[i].z), "=r"(w[i].w) : "l"(wp + (size_t)i * 64 * (NH * DH)));
        float* xn = reinterpret_cast<float*>(smem + OFF_XN);
        if (warp < 4) {
            uint32_t v[9];
            const uint32_t* xp = reinterpret_cast<const uint32_t*>(x + warp * DM);
#pragma unroll
            for (int i = 0; i < 9; i++) v[i] = __ldg(xp + lane + 32 * i);
            warp_layernorm(v);
#pragma unroll
            for (int i = 0; i < 9; i++) {
                xn[(2 * (lane + 32 * i)) * 4 + warp] = bf_lo(v[i]);
                xn[(2 * (lane + 32 * i) + 1) * 4 + warp] = bf_hi(v[i]);
            }
        }
        cons_bar();
        float a[32];
#pragma unroll
        for (int i = 0; i < 32; i++) a[i] = 0.f;
#pragma unroll
        for (int i = 0; i < 9; i++) {
            const float4 xv = *reinterpret_cast<const float4*>(xn + ((tid >> 2) + 64 * i) * 4);
            const float wf[8] = {bf_lo(w[i].x), bf_hi(w[i].x), bf_lo(w[i].y), bf_hi(w[i].y),
                                 bf_lo(w[i].z), bf_hi(w[i].z), bf_lo(w[i].w), bf_hi(w[i].w)};
#pragma unroll
            for (int e = 0; e < 8; e++) {
                a[e] = fmaf(xv.x, wf[e], a[e]);
                a[8 + e] = fmaf(xv.y, wf[e], a[8 + e]);
                a[16 + e] = fmaf(xv.z, wf[e], a[16 + e]);
                a[24 + e] = fmaf(xv.w, wf[e], a[24 + e]);
            }
        }
        {
            const bool b4 = lane & 16, b3 = lane & 8, b2 = lane & 4;
#pragma unroll
            for (int i = 0; i < 16; i++) { const float s = b4 ? a[i] : a[i + 16], k = b4 ? a[i + 16] : a[i]; a[i] = k + __shfl_xor_sync(0xffffffffu, s, 16); }
#pragma unroll
            for (int i = 0; i < 8; i++) { const float s = b3 ? a[i] : a[i + 8], k = b3 ? a[i + 8] : a[i]; a[i] = k + __shfl_xor_sync(0xffffffffu, s, 8); }
#pragma unroll
            for (int i = 0; i < 4; i++) { const float s = b2 ? a[i] : a[i + 4], k = b2 ? a[i + 4] : a[i]; a[i] = k + __shfl_xor_sync(0xffffffffu, s, 4); }
            float* qred = reinterpret_cast<float*>(smem + OFF_QRED);
            const int b = (lane >> 3) & 3;
            *reinterpret_cast<float4*>(qred + warp * 128 + b * 32 + (lane & 3) * 8 + (b2 ? 4 : 0)) = make_float4(a[0], a[1], a[2], a[3]);
        }
        cons_bar();
        if (tid < 64) {
            const float2* qred = reinterpret_cast<const float2*>(smem + OFF_QRED);
            float s0 = 0.f, s1 = 0.f;
#pragma unroll
            for (int w8 = 0; w8 < 8; w8++) { const float2 v = qred[w8 * 64 + tid]; s0 += v.x; s1 += v.y; }
            st_rlx(g_q + ((tid >> 4) * NH + (cta >> 2)) * 64 + (cta & 3) * 16 + (tid & 15), nzb(pack_bf2(s0, s1)));
        }
    }
    asm volatile("bar.sync 2, 384;" ::: "memory");
    asm volatile("setmaxnreg.inc.sync.aligned.u32 216;");

    uint32_t offK[4], offV[4];
    {
        const int i = lane & 7;
        const uint32_t rk = (16 * warp + i + 8 * ((lane >> 3) & 1)) * 256, xk = (lane >> 4) ^ i;
        const uint32_t rv = (16 * warp + i + 8 * (lane >> 4)) * 256, xv = ((lane >> 3) & 1) ^ i;
#pragma unroll
        for (int j = 0; j < 4; j++) { offK[j] = rk + (((2 * j) ^ xk) << 4); offV[j] = rv + (((2 * j) ^ xv) << 4) + TILE_BYTES; }
    }
    const bool valid = (c == (g >> 1));
    const bool odd = g & 1;
    int p = 0, n = 0;
    uint32_t ph = 0;
    for (;; n++) {
        mbar_wait(bars + (BAR_DESC + (n & 7)) * 8, (n >> 3) & 1);
        if (desc[n & 7].y == 0) break;
        uint32_t qf[8][2];
        {
            uint2* qs = reinterpret_cast<uint2*>(smem + OFF_Q + (n & 7) * 256) + lane;
            uint2 qv = *qs;
            if (!__all_sync(0xffffffffu, qv.x && qv.y)) {
                uint32_t spins = 0;
                while (!(qv.x && qv.y)) { qv = ld_rlx2(g_q + desc[n & 7].x * 64 + 2 * lane); spin_guard(spins); }
                *qs = qv;
                __syncwarp();
            }
            const uint32_t qa = sb + OFF_Q + (n & 7) * 256 + c * 4;
#pragma unroll
            for (int j = 0; j < 8; j++) { qf[j][0] = lds32(qa + (((2 * j) ^ g) << 4)); qf[j][1] = lds32(qa + (((2 * j + 1) ^ g) << 4)); }
        }
        const uint32_t base = sb + 2 * p * TILE_BYTES;
        float* r = reinterpret_cast<float*>(smem + OFF_RED) + ((n & 1) * 8 + warp) * PART_STRIDE;
        mbar_wait(bars + (BAR_FULL + 2 * p) * 8, ph);
        float sa[4] = {0.f, 0.f, 0.f, 0.f}, sc[4] = {0.f, 0.f, 0.f, 0.f};
        {
            uint32_t a[8][4];
#pragma unroll
            for (int j = 0; j < 8; j++) ldsm4(a[j], base + offK[j & 3] + (j >> 2) * 128);
#pragma unroll
            for (int j = 0; j < 8; j += 2) { mma16816(sa, a[j], qf[j][0], qf[j][1]); mma16816(sc, a[j + 1], qf[j + 1][0], qf[j + 1][1]); }
        }
        const uint32_t r1 = pack_bf2(odd ? sa[1] + sc[1] : sa[0] + sc[0], odd ? sa[3] + sc[3] : sa[2] + sc[2]);
        __syncwarp();
        if (lane == 0) mbar_arrive_after(bars + (BAR_EMPTY + 2 * p) * 8, r1);
        const uint32_t r2 = pack_bf2(bf_lo(r1) * SM_SCALE, bf_hi(r1) * SM_SCALE);
        const float s0 = valid ? bf_lo(r2) : -INFINITY, s1 = valid ? bf_hi(r2) : -INFINITY;
        const float m = warp_max(fmaxf(s0, s1));
        const float p0 = ex2((s0 - m) * LOG2E), p1 = ex2((s1 - m) * LOG2E);
        const uint32_t pp = pack_bf2(p0, p1);
        const uint32_t pb0 = odd ? pp << 16 : pp & 0xffffu;
        const uint32_t pb1 = odd ? pp & 0xffff0000u : pp >> 16;
        const float l = warp_sum(p0 + p1);
        mbar_wait(bars + (BAR_RFREE + (n & 1)) * 8, ((n >> 1) & 1) ^ 1);
        if (lane == 0) { *reinterpret_cast<float2*>(r + 128) = make_float2(m, l); mbar_arrive(bars + (BAR_MFULL + (n & 1)) * 8); }
        mbar_wait(bars + (BAR_FULL + 2 * p + 1) * 8, ph);
        float acc[8][4];
        {
            uint32_t a[8][4];
#pragma unroll
            for (int j = 0; j < 8; j++) ldsm4t(a[j], base + offV[j & 3] + (j >> 2) * 128);
#pragma unroll
            for (int j = 0; j < 8; j++) { acc[j][0] = acc[j][1] = acc[j][2] = acc[j][3] = 0.f; mma16816(acc[j], a[j], pb0, pb1); }
        }
        float ev[8], od[8];
#pragma unroll
        for (int j = 0; j < 8; j++) { ev[j] = acc[j][0] + acc[j][3]; od[j] = acc[j][1] + acc[j][2]; }
#pragma unroll
        for (int j = 0; j < 8; j += 2) { ev[j] += __shfl_xor_sync(0xffffffffu, ev[j + 1], 1); od[j] += __shfl_xor_sync(0xffffffffu, od[j + 1], 1); }
#pragma unroll
        for (int j = 0; j < 8; j += 4) { ev[j] += __shfl_xor_sync(0xffffffffu, ev[j + 2], 2); od[j] += __shfl_xor_sync(0xffffffffu, od[j + 2], 2); }
        r[16 * c + g] = ev[0]; r[16 * c + 8 + g] = od[0];
        r[64 + 16 * c + g] = ev[4]; r[64 + 16 * c + 8 + g] = od[4];
        __syncwarp();
        if (lane == 0) {
            mbar_arrive(bars + (BAR_RFULL + (n & 1)) * 8);
            mbar_arrive_after(bars + (BAR_EMPTY + 2 * p + 1) * 8, __float_as_uint(ev[0]) ^ __float_as_uint(ev[4]));
        }
        if (++p == NPAIR) { p = 0; ph ^= 1; }
    }

    const uint32_t tag = *reinterpret_cast<volatile uint32_t*>(smem + OFF_TAG);
    const uint32_t z = *reinterpret_cast<volatile uint32_t*>(smem + OFF_TAG + 4);
    const uint32_t reg0 = sb + 2 * ((n + 0) % NPAIR) * TILE_BYTES;
    const uint32_t reg1 = sb + 2 * ((n + 1) % NPAIR) * TILE_BYTES;
    const uint32_t reg2 = sb + 2 * ((n + 2) % NPAIR) * TILE_BYTES;
    if (!is_ffn) {
        const int own = cta - N_FFN;
        const int ob = (tid >> 3) & 3, opr = tid & 7;
        const uint32_t xw = __ldg(reinterpret_cast<const uint32_t*>(x + ob * DM + own * 16 + 2 * opr));
        const float* p_att = pin(g_att + own * NH * 64 + tid * 4, z);
        uint32_t* p_h = pin(g_h + ((tid >> 5) * NB + ob) * (DM / 2) + own * 8 + opr, z);
        const int b = tid >> 6, dp = tid & 63;
        float* gp = g_part + (b * NH + own) * PART_STRIDE;
        float* gl = g_part + (NBH + own * NLAST + 2 * warp) * PART_STRIDE;
        if (is_wo) {
            float* p_st = pin(g_att + (warp * NH + own) * 64 + (g + 8 * (c >> 1)) * 4 + 2 * (c & 1), z);
            wait_ready<N_OWN>(lane, tag);
            uint32_t spins = 0;
            if (b < NB - 1) {
                uint2 ml, ov;
                do { ml = ld_rlx2<512>(gp); ov = ld_rlx2(gp + 2 * dp); spin_guard(spins); } while (!(ml.x && ml.y && ov.x && ov.y));
                const float inv = __fdividef(1.0f, __uint_as_float(ml.y));
                *reinterpret_cast<uint32_t*>(smem + OFF_OB + (b * OB_PITCH + 2 * dp) * 2) =
                    pack_bf2(__uint_as_float(ov.x) * inv, __uint_as_float(ov.y) * inv);
            }
            __syncwarp();
            uint32_t wf[8][5][4];
#pragma unroll
            for (int ks = 0; ks < 8; ks++) {
                mbar_wait(bars + (BAR_W + ks) * 8, 0);
                rows_load(wf[ks], (ks < 3 ? reg0 : ks < 6 ? reg1 : reg2) + (ks % 3) * W_PIECE, warp, lane);
            }
            float* lred = reinterpret_cast<float*>(smem + OFF_GU);
            {
                const float* g3 = g_part + ((NB - 1) * NH + own) * PART_STRIDE;
                uint2 ml[3];
                uint4 ov[3];
                ml[2] = make_uint2(0xff800000u, 1u); ov[2] = make_uint4(1u, 1u, 1u, 1u);
                uint32_t pending = warp == 0 ? 7u : 3u;
                while (true) {
                    if (pending & 1) { ml[0] = ld_rlx2<512>(gl); ov[0] = ld_rlx4(gl + 4 * lane); }
                    if (pending & 2) { ml[1] = ld_rlx2<PART_STRIDE * 4 + 512>(gl); ov[1] = ld_rlx4<PART_STRIDE * 4>(gl + 4 * lane); }
                    if (pending & 4) { ml[2] = ld_rlx2<512>(g3); ov[2] = ld_rlx4(g3 + 4 * lane); }
#pragma unroll
                    for (int i = 0; i < 3; i++)
                        if (ml[i].x && ml[i].y && ok4(ov[i])) pending &= ~(1u << i);
                    if (!__any_sync(0xffffffffu, pending)) break;
                    spin_guard(spins);
                }
                const float M = fmaxf(fmaxf(__uint_as_float(ml[0].x), __uint_as_float(ml[1].x)), __uint_as_float(ml[2].x));
                float4 o = make_float4(0.f, 0.f, 0.f, 0.f);
                float L = 0.f;
#pragma unroll
                for (int i = 0; i < 3; i++) {
                    const float f = ex2((__uint_as_float(ml[i].x) - M) * LOG2E);
                    L = fmaf(f, __uint_as_float(ml[i].y), L);
                    o.x = fmaf(f, __uint_as_float(ov[i].x), o.x); o.y = fmaf(f, __uint_as_float(ov[i].y), o.y);
                    o.z = fmaf(f, __uint_as_float(ov[i].z), o.z); o.w = fmaf(f, __uint_as_float(ov[i].w), o.w);
                }
                *reinterpret_cast<float4*>(lred + warp * PART_STRIDE + 4 * lane) = o;
                if (lane == 0) *reinterpret_cast<float2*>(lred + warp * PART_STRIDE + 128) = make_float2(M, L);
            }
            cons_bar();
            if (tid < 64) {
                float2 ml[8], ov[8];
#pragma unroll
                for (int w8 = 0; w8 < 8; w8++) {
                    ml[w8] = *reinterpret_cast<const float2*>(lred + w8 * PART_STRIDE + 128);
                    ov[w8] = *reinterpret_cast<const float2*>(lred + w8 * PART_STRIDE + 2 * tid);
                }
                const float M = fmaxf(fmaxf(fmaxf(ml[0].x, ml[1].x), fmaxf(ml[2].x, ml[3].x)), fmaxf(fmaxf(ml[4].x, ml[5].x), fmaxf(ml[6].x, ml[7].x)));
                float L[2] = {0.f, 0.f}, o0[2] = {0.f, 0.f}, o1[2] = {0.f, 0.f};
#pragma unroll
                for (int w8 = 0; w8 < 8; w8++) {
                    const float f = ex2((ml[w8].x - M) * LOG2E);
                    L[w8 & 1] = fmaf(f, ml[w8].y, L[w8 & 1]);
                    o0[w8 & 1] = fmaf(f, ov[w8].x, o0[w8 & 1]);
                    o1[w8 & 1] = fmaf(f, ov[w8].y, o1[w8 & 1]);
                }
                const float inv = __fdividef(1.0f, L[0] + L[1]);
                *reinterpret_cast<uint32_t*>(smem + OFF_OB + ((NB - 1) * OB_PITCH + 2 * tid) * 2) =
                    pack_bf2((o0[0] + o0[1]) * inv, (o1[0] + o1[1]) * inv);
            }
            cons_bar();
            float acc[5][4];
#pragma unroll
            for (int i = 0; i < 5; i++) { acc[i][0] = acc[i][1] = acc[i][2] = acc[i][3] = 0.f; }
            rows_mma<8>(acc, wf, sb + OFF_OB + ((g & 3) * OB_PITCH + 2 * c) * 2, warp, lane);
            rows_store<8 * NH * 256>(acc, p_st, warp, lane);
        } else {
            mbar_wait(bars + BAR_CLEAN * 8, 0);
        }
        float* ored = reinterpret_cast<float*>(smem + OFF_GU);
        {
            const float4 a = gather_sum<2>(p_att);
            const bool hi = tid & 16;
            const float u0 = (hi ? a.z : a.x) + __shfl_xor_sync(0xffffffffu, hi ? a.x : a.z, 16);
            const float u1 = (hi ? a.w : a.y) + __shfl_xor_sync(0xffffffffu, hi ? a.y : a.w, 16);
            float* r = ored + warp * 64 + (hi ? 32 : 0) + (tid & 15);
            r[0] = u0; r[16] = u1;
        }
        cons_bar();
        if (tid < 32 * H_REP) {
            const float2 a = warps_sum<64>(ored + ob * 16 + 2 * opr);
            const uint32_t ar = pack_bf2(a.x, a.y);
            put(p_h, nzb(pack_bf2(bf_lo(xw) + bf_lo(ar), bf_hi(xw) + bf_hi(ar))));
        }
        if (is_wo) {
            cons_bar();
            st_rlx2(gp + 2 * dp, 0, 0);
            if (dp == 0) st_rlx2(gp + 128, 0, 0);
            st_rlx4(gl + 4 * lane, 0, 0, 0, 0);
            st_rlx4(gl + PART_STRIDE + 4 * lane, 0, 0, 0, 0);
            if (lane < 2) st_rlx2(gl + lane * PART_STRIDE + 128, 0, 0);
            st_rlx(g_q + (b * NH + own) * 64 + dp, 0);
        }
    } else {
        float* p_st = pin(g_y + ((2 * warp + (c >> 1)) * N_FFN + cta) * 32 + g * 4 + 2 * (c & 1), z);
        const float* p_y = pin(g_y + cta * N_FFN * 32 + tid * 4, z);
        uint32_t* p_out = pin(reinterpret_cast<uint32_t*>(out + ((tid >> 2) & 3) * DM + cta * 8 + 2 * (tid & 3)), z);
        const uint32_t* hp = pin(g_h + ((cta & (H_REP - 1)) * NB + (warp & 3)) * (DM / 2) + lane, z);
        if (warp < 4) wait_ready<N_OWN + N_OUT>(lane, tag);
        uint32_t wf[9][3][4];
        const uint32_t arow = ((warp >> 2) ? reg1 : reg0) + ((warp & 3) * GU_BOXROWS + (lane & 7) + 8 * (lane >> 4)) * GU_PITCH + ((lane >> 3) & 1) * 16;
        volatile uint32_t* flags = reinterpret_cast<volatile uint32_t*>(smem + OFF_STAT + 32);
        bool have = true;
        if (warp < 4) mbar_wait(bars + (BAR_W + warp) * 8, 0);
        else {
            uint32_t spins = 0;
            while (!(have = mbar_test(bars + (BAR_W + warp) * 8, 0)) && flags[1] != tag) { if (++spins > (1u << 27)) die(); }
            have = __all_sync(0xffffffffu, have);
        }
        if (have) {
#pragma unroll
            for (int ks = 0; ks < 9; ks++)
#pragma unroll
                for (int i = 0; i < 3; i++) ldsm4t(wf[ks][i], arow + ks * 16 * GU_PITCH + i * 32);
        }
        if (warp < 4) {
            uint32_t spins = 0;
            if (warp == 0) {
                const uint32_t* pp = hp - lane + (lane % H_ARM) * (DM / 2 / H_ARM) + (cta >> 2);
                while (!__any_sync(0xffffffffu, lane < H_ARM && ld_rlx(pp))) spin_guard(spins);
                if (lane == 0) flags[0] = tag;
            } else {
                while (flags[0] != tag) { if (++spins > (1u << 27)) die(); }
                spins = 0;
            }
            uint32_t hw[9];
#pragma unroll
            for (int i = 0; i < 9; i++) hw[i] = 0;
            while (true) {
                static_for<9>([&](auto I) { constexpr int i = decltype(I)::value; if (!hw[i]) hw[i] = ld_rlx<i * 128>(hp); });
                bool ok = true;
#pragma unroll
                for (int i = 0; i < 9; i++) ok = ok && hw[i];
                if (__all_sync(0xffffffffu, ok)) break;
                spin_guard(spins);
            }
            if (lane == 0) flags[1] = tag;
            uint32_t* hn = reinterpret_cast<uint32_t*>(smem + OFF_HN) + warp * (HN_PITCH / 2);
#pragma unroll
            for (int i = 0; i < 9; i++) hn[lane + 32 * i] = hw[i];
        }
        asm volatile("bar.sync 5, 320;" ::: "memory");
        {
            const uint32_t hb = sb + OFF_HN + ((g & 3) * HN_PITCH + (warp & 3) * GU_BOXROWS + 2 * c) * 2;
            uint32_t bf[9][2];
#pragma unroll
            for (int ks = 0; ks < 9; ks++) {
                bf[ks][0] = lds32(hb + ks * 32); bf[ks][1] = lds32(hb + ks * 32 + 16);
                if (g == 4) bf[ks][0] = bf[ks][1] = 0x3f803f80u;
            }
            if (!have) {
                mbar_wait(bars + (BAR_W + warp) * 8, 0);
#pragma unroll
                for (int ks = 0; ks < 9; ks++)
#pragma unroll
                    for (int i = 0; i < 3; i++) ldsm4t(wf[ks][i], arow + ks * 16 * GU_PITCH + i * 32);
            }
            float acc[2][3][4];
#pragma unroll
            for (int i = 0; i < 6; i++) { acc[i / 3][i % 3][0] = acc[i / 3][i % 3][1] = acc[i / 3][i % 3][2] = acc[i / 3][i % 3][3] = 0.f; }
#pragma unroll
            for (int ks = 0; ks < 9; ks++)
#pragma unroll
                for (int i = 0; i < 3; i++) mma16816(acc[ks & 1][i], wf[ks][i], bf[ks][0], bf[ks][1]);
            float* gu = reinterpret_cast<float*>(smem + OFF_GU) + (warp * FC + g) * 6 + 2 * c;
            if (c < 3) {
#pragma unroll
                for (int i = 0; i < 3; i++) {
                    *reinterpret_cast<float2*>(gu + i * 96) = make_float2(acc[0][i][0] + acc[1][i][0], acc[0][i][1] + acc[1][i][1]);
                    *reinterpret_cast<float2*>(gu + i * 96 + 48) = make_float2(acc[0][i][2] + acc[1][i][2], acc[0][i][3] + acc[1][i][3]);
                }
            }
        }
        asm volatile("bar.sync 6, 320;" ::: "memory");
        if (tid < FC * 4) {
            const float* gu = reinterpret_cast<const float*>(smem + OFF_GU) + (tid >> 2) * 6;
            const float2 st = reinterpret_cast<const float2*>(smem + OFF_STAT)[tid & 3];
            float v[8], cs[8];
#pragma unroll
            for (int k = 0; k < 8; k++) { v[k] = gu[k * FC * 6 + (tid & 3)]; cs[k] = gu[k * FC * 6 + 4]; }
            const float gr = fmaf(-st.x, (cs[0] + cs[1]) + (cs[2] + cs[3]), (v[0] + v[1]) + (v[2] + v[3])) * st.y;
            const float ur = fmaf(-st.x, (cs[4] + cs[5]) + (cs[6] + cs[7]), (v[4] + v[5]) + (v[6] + v[7])) * st.y;
            const uint32_t r = pack_bf2(gr, ur);
            const float gs = bf_lo(r), us = bf_hi(r);
            constexpr float K1 = -2.0f * LOG2E * 0.7978845608028654f, K3 = K1 * 0.044715f;
            float rc;
            asm("rcp.approx.ftz.f32 %0, %1;" : "=f"(rc) : "f"(1.0f + ex2(gs * fmaf(gs * gs, K3, K1))));
            const float ge = bf16r(gs * rc);
            reinterpret_cast<__nv_bfloat16*>(smem + OFF_ACT)[(tid & 3) * ACT_PITCH + (tid >> 2)] = __float2bfloat16_rn(ge * us);
        }
        uint32_t wdf[2][5][4], wdl[1][5][4];
        const uint32_t ab = sb + OFF_ACT + ((g & 3) * ACT_PITCH + 2 * c) * 2;
#pragma unroll
        for (int ks = 0; ks < 2; ks++) mbar_wait(bars + (BAR_W + 8 + ks) * 8, 0);
#pragma unroll
        for (int ks = 0; ks < 2; ks++) rows_load(wdf[ks], reg2 + ks * W_PIECE, warp, lane);
        cons_bar();
        float acc[5][4];
#pragma unroll
        for (int i = 0; i < 5; i++) { acc[i][0] = acc[i][1] = acc[i][2] = acc[i][3] = 0.f; }
        rows_mma<2>(acc, wdf, ab, warp, lane);
        mbar_wait(bars + (BAR_W + 10) * 8, 0);
        rows_load(wdl[0], reg2 + 2 * W_PIECE, warp, lane);
        rows_mma<1>(acc, wdl, ab + 64, warp, lane);
        rows_store<16 * N_FFN * 128>(acc, p_st, warp, lane);
        if (cta < N_OUT) {
            const float4 a = gather_sum<3>(p_y);
            const bool b4 = lane & 16, b3 = lane & 8;
            const float u0 = (b4 ? a.z : a.x) + __shfl_xor_sync(0xffffffffu, b4 ? a.x : a.z, 16);
            const float u1 = (b4 ? a.w : a.y) + __shfl_xor_sync(0xffffffffu, b4 ? a.y : a.w, 16);
            float* yred = reinterpret_cast<float*>(smem + OFF_GU);
            yred[tid] = (b3 ? u1 : u0) + __shfl_xor_sync(0xffffffffu, b3 ? u0 : u1, 8);
            cons_bar();
            if (tid < 16) {
                const float2 y = warps_sum<32>(yred + (tid >> 2) * 8 + 2 * (tid & 3));
                const uint32_t hr = reinterpret_cast<const uint32_t*>(smem + OFF_HN)[(tid >> 2) * (HN_PITCH / 2) + cta * 4 + (tid & 3)];
                const uint32_t yr = pack_bf2(y.x, y.y);
                *p_out = pack_bf2(bf_lo(hr) + bf_lo(yr), bf_hi(hr) + bf_hi(yr));
            }
        }
    }
}

typedef CUresult (*EncodeFn)(CUtensorMap*, CUtensorMapDataType, cuuint32_t, void*, const cuuint64_t*, const cuuint64_t*,
                             const cuuint32_t*, const cuuint32_t*, CUtensorMapInterleave, CUtensorMapSwizzle,
                             CUtensorMapL2promotion, CUtensorMapFloatOOBfill);

bool make_map(EncodeFn enc, CUtensorMap* m, const void* ptr) {
    const cuuint64_t dims[2] = {(cuuint64_t)DF, (cuuint64_t)DM};
    const cuuint64_t strides[1] = {(cuuint64_t)DF * 2};
    const cuuint32_t box[2] = {GU_PITCH / 2, GU_BOXROWS};
    const cuuint32_t estr[2] = {1, 1};
    return enc(m, CU_TENSOR_MAP_DATA_TYPE_BFLOAT16, 2, const_cast<void*>(ptr), dims, strides, box, estr,
               CU_TENSOR_MAP_INTERLEAVE_NONE, CU_TENSOR_MAP_SWIZZLE_NONE, CU_TENSOR_MAP_L2_PROMOTION_L2_128B,
               CU_TENSOR_MAP_FLOAT_OOB_FILL_NONE) == CUDA_SUCCESS;
}

bool make_row_map(EncodeFn enc, CUtensorMap* m, const void* ptr, int rows) {
    const cuuint64_t dims[3] = {64, 9, (cuuint64_t)rows};
    const cuuint64_t strides[2] = {128, (cuuint64_t)DM * 2};
    const cuuint32_t box[3] = {64, 9, 16};
    const cuuint32_t estr[3] = {1, 1, 1};
    return enc(m, CU_TENSOR_MAP_DATA_TYPE_BFLOAT16, 3, const_cast<void*>(ptr), dims, strides, box, estr,
               CU_TENSOR_MAP_INTERLEAVE_NONE, CU_TENSOR_MAP_SWIZZLE_128B, CU_TENSOR_MAP_L2_PROMOTION_NONE,
               CU_TENSOR_MAP_FLOAT_OOB_FILL_NONE) == CUDA_SUCCESS;
}

}

extern "C" void kernel_launch(void* const* d_in, const int* in_sizes, int n_in, void* d_out, int out_size) {
    (void)in_sizes; (void)n_in; (void)out_size;
    const __nv_bfloat16* x = (const __nv_bfloat16*)d_in[0];
    const __nv_bfloat16* kc = (const __nv_bfloat16*)d_in[1];
    const __nv_bfloat16* vc = (const __nv_bfloat16*)d_in[2];
    const __nv_bfloat16* wq = (const __nv_bfloat16*)d_in[3];
    const __nv_bfloat16* wo = (const __nv_bfloat16*)d_in[4];
    const void* wg = d_in[6];
    const void* wu = d_in[7];
    const __nv_bfloat16* wd = (const __nv_bfloat16*)d_in[8];

    static EncodeFn enc = nullptr;
    static int sms = 0;
    if (!enc) {
        void* fn = nullptr;
        cudaDriverEntryPointQueryResult qr;
        cudaGetDriverEntryPoint("cuTensorMapEncodeTiled", &fn, cudaEnableDefault, &qr);
        enc = (EncodeFn)fn;
        int dev = 0;
        cudaGetDevice(&dev);
        cudaDeviceGetAttribute(&sms, cudaDevAttrMultiProcessorCount, dev);
        cudaFuncSetAttribute(decode_layer_kernel, cudaFuncAttributeMaxDynamicSharedMemorySize, SMEM_BYTES);
    }
    if (!enc || sms < GRID) return;
    CUtensorMap mg, mu, md, mo;
    if (!make_map(enc, &mg, wg) || !make_map(enc, &mu, wu) || !make_row_map(enc, &md, wd, DF) || !make_row_map(enc, &mo, wo, NH * DH)) return;
    decode_layer_kernel<<<GRID, NTHREADS, SMEM_BYTES, cudaStreamPerThread>>>(x, kc, vc, wq, (__nv_bfloat16*)d_out, mg, mu, md, mo);
}
```
